```python
import torch

def _softmax(x, axis=-1):
    return torch.softmax(x, dim=axis)
def _gelu(x):
    return torch.nn.functional.gelu(x, approximate="tanh")
def _silu(x):
    return torch.nn.functional.silu(x)
def _sigmoid(x):
    return torch.sigmoid(x)
def _layernorm(x, axis=-1, eps=1e-5):
    m = x.mean(dim=axis, keepdim=True)
    v = x.var(dim=axis, keepdim=True, unbiased=False)
    return (x - m) / torch.sqrt(v + eps)
def _scatter_add(tgt, idx, src, axis=0):
    return tgt.clone().index_add_(axis, idx, src)
def _segment_sum(src, seg, n):
    out = torch.zeros((n,) + src.shape[1:], dtype=src.dtype)
    return out.index_add_(0, seg, src)
def _pad(x, pw):
    flat = tuple(v for pair in reversed(pw) for v in pair)
    return torch.nn.functional.pad(x, flat)

kernel_name = 'gated_mix__compressed_kv_cla__mixer_token_mlp__decode'

def setup_inputs():

    _w = (lambda a: (lambda t: t.to(torch.bfloat16) if t.is_floating_point() else t)(torch.as_tensor(a)))
    def _A_setup():
        B, H, Sq, Sk, D, M = 4, 32, 1, 4096, 128, 576
        Dc = 4 * D
        return {
            "x": _w((lambda *s: torch.randn(*s, dtype=torch.bfloat16) * 0.05)(B, Sq, M)),
            "c_kv": _w((lambda *s: torch.randn(*s, dtype=torch.bfloat16) * 0.4)(B, Sk, Dc)),
            "w_q": _w((lambda *s: torch.randn(*s, dtype=torch.bfloat16) * 3.2)(M, H, D) * (M ** -0.5)),
            "w_uk": _w((lambda *s: torch.randn(*s, dtype=torch.bfloat16) * 3.2)(Dc, H, D) * (Dc ** -0.5)),
            "w_uv": _w((lambda *s: torch.randn(*s, dtype=torch.bfloat16) * 0.4)(Dc, H, D) * (Dc ** -0.5)),
            "w_o": _w((lambda *s: torch.randn(*s, dtype=torch.bfloat16) * 0.4)(H, D, M) * ((H * D) ** -0.5)),
        }
    _A_in = _A_setup()

    def _B_setup():
        B, S, D, F = 4, 1, 576, 4608
        return {
            "x": _w((lambda *s: torch.randn(*s, dtype=torch.bfloat16) * 0.05)(B, S, D)),
            "w1": _w((lambda *s: torch.randn(*s, dtype=torch.bfloat16) * 0.05)(S, F) * (S ** -0.5)),
            "b1": _w((lambda *s: torch.randn(*s, dtype=torch.bfloat16) * 0.05)(F) * 0.02),
            "w2": _w((lambda *s: torch.randn(*s, dtype=torch.bfloat16) * 0.05)(F, S) * (F ** -0.5)),
            "b2": _w((lambda *s: torch.randn(*s, dtype=torch.bfloat16) * 0.05)(S) * 0.02),
        }
    _B_in = _B_setup()

    return {
        "A_x": _A_in["x"],
        "A_c_kv": _A_in["c_kv"],
        "A_w_q": _A_in["w_q"],
        "A_w_uk": _A_in["w_uk"],
        "A_w_uv": _A_in["w_uv"],
        "A_w_o": _A_in["w_o"],
        "B_x": _B_in["x"],
        "B_w1": _B_in["w1"],
        "B_b1": _B_in["b1"],
        "B_w2": _B_in["w2"],
        "B_b2": _B_in["b2"],
        "gate_w": _w((lambda *s: torch.randn(*s, dtype=torch.bfloat16) * 0.05)(576) * 16.0),
    }

def reference(A_x, A_c_kv, A_w_q, A_w_uk, A_w_uv, A_w_o, B_x, B_w1, B_b1, B_w2, B_b2, gate_w):
    def _A_ref(x, c_kv, w_q, w_uk, w_uv, w_o):
        B, Sq, M = x.shape[0], x.shape[1], x.shape[2]
        Sk = c_kv.shape[1]
        H, D = w_q.shape[1], w_q.shape[2]
        q = torch.einsum("bqm,mhd->bhqd", x, w_q)
        k = torch.einsum("bkc,chd->bhkd", c_kv, w_uk)
        v = torch.einsum("bkc,chd->bhkd", c_kv, w_uv)
        scores = torch.einsum("bhqd,bhkd->bhqk", q, k) * (D ** -0.5)
        off = Sk - Sq
        qi = torch.arange(Sq)[:, None]
        kj = torch.arange(Sk)[None, :]
        cmask = kj <= (qi + off)
        scores = torch.where(cmask[None, None], scores, -1e9)
        p = _softmax(scores, axis=-1)
        ctx = torch.einsum("bhqk,bhkd->bhqd", p, v)
        return torch.einsum("bhqd,hdm->bqm", ctx, w_o)

    def _B_ref(x, w1, b1, w2, b2):
        B, S, D = x.shape
        h = _layernorm(x, axis=-1)
        u = torch.einsum("bsd,sf->bdf", h, w1) + b1
        u = _gelu(u)
        y = torch.einsum("bdf,fs->bds", u, w2) + b2
        return (lambda x, *d: x.permute(*d))(y, 0, 2, 1)

    x = A_x
    g = _sigmoid((x * gate_w).sum(-1, keepdims=True))
    a = _A_ref(x, A_c_kv, A_w_q, A_w_uk, A_w_uv, A_w_o)
    b = _B_ref(x, B_w1, B_b1, B_w2, B_b2)
    return g * a + (1 - g) * b
```

```cpp
#include <cuda_runtime.h>
#include <cuda_bf16.h>
#include <cuda.h>
#include <stdint.h>

namespace {

constexpr int NB = 4, NH = 32, SK = 4096, DH = 128, DM = 576, DC = 512, NF = 4608;
constexpr int NCTA = 128;
constexpr int NTHREADS = 640;
constexpr int FPH = NF / NH;
constexpr int MQ = DM / 4;
constexpr int WOP = 304;

#define SWAP 0
#define STAGGER 0
#define NTMAX 9
#define PSLEEP 0
#define RATE 25.0f
#define LEAD 600
#define WKEARLY 2
#define SPAN1 98304
#define TAILSLOW 1.0f
#define TAILGAP 0
#define TAPER 0
#define PHASE 1
#define WMAX 6
#define REG_A 120
#define REG_W 96
#define REG_P 40
constexpr int SPIN_LIMIT = 1 << 20;

constexpr int OFF_C = 0;
constexpr int OFF_PD = 40960;
constexpr int OFF_WQ = 65536;
constexpr int OFF_Q = 131072;
constexpr int OFF_MA = OFF_WQ + 36864;
constexpr int OFF_WUV = OFF_Q + 32768;
constexpr int OFF_P = OFF_WUV + 32768;
constexpr int OFF_MB = OFF_P;
constexpr int OFF_Y = OFF_P + 9216;
constexpr int OFF_STAGE = OFF_Y + 4608;
constexpr int OFF_QS = OFF_STAGE + 2048;
constexpr int OFF_BM = OFF_QS + 1024;
constexpr int OFF_X = OFF_BM + 1024;
constexpr int OFF_GW = OFF_X + 4608;
constexpr int OFF_RAW = OFF_GW + 1152;
constexpr int OFF_STAT = OFF_RAW + 864;
constexpr int OFF_GATE = OFF_STAT + 128;
constexpr int OFF_EPOCH = OFF_GATE + 16;
constexpr int OFF_PM = OFF_EPOCH + 16;
constexpr int OFF_PL = OFF_PM + 256;
constexpr int OFF_MX = OFF_PL + 128;
constexpr int OFF_LSUM = OFF_MX + 1024;
constexpr int OFF_BAR = OFF_LSUM + 1024;
constexpr int SMEM_BYTES = OFF_BAR + 384, NSTART = 576;
static_assert(SMEM_BYTES <= 232448, "shared memory budget");

constexpr int NPIECE = 18;
constexpr int BAR_WQ = 0, BAR_WK = 2, BAR_C = 4, BAR_UV = 12, BAR_WO = 14;
constexpr int BAR_C0FREE = 18;
constexpr int BAR_WKFREE = 19;
constexpr int BAR_LATE = 20;
constexpr int BAR_Q = 21;
constexpr int BAR_PM = 22;
constexpr int BAR_PD = 23;
constexpr int BAR_PF = 25;
constexpr int BAR_PL = 26;
constexpr int NBAR = 27;
constexpr float LAZY_LIMIT = 1024.f;

struct Scratch {
    uint4 e3[NCTA * 64 * 16];
    uint4 e5[72 * NH * 8];
    uint4 e1[NCTA * 128];
    uint4 e4[NCTA * 128];
    uint4 e2[2 * NB * 2048];
    uint2 stats[NCTA * 16];
    uint32_t c3[NB * 16 * 32];
    uint32_t c2[32];
    uint32_t epoch[NCTA * 32];
};
__device__ __align__(1024) Scratch g_scratch;
#define TLARG
#define TLPASS
#define TLM(i) do {} while (0)
#define TLG(i) do {} while (0)
#define TLV(i, v) do {} while (0)
#define TL(i) do {} while (0)

__device__ __forceinline__ uint32_t smem_u32(const void* p) { return (uint32_t)__cvta_generic_to_shared(p); }
__device__ __forceinline__ void mbar_init(uint32_t bar, int cnt) {
    asm volatile("mbarrier.init.shared::cta.b64 [%0], %1;" ::"r"(bar), "r"(cnt) : "memory");
}
__device__ __forceinline__ void mbar_expect_tx(uint32_t bar, uint32_t bytes) {
    asm volatile("mbarrier.arrive.expect_tx.shared::cta.b64 _, [%0], %1;" ::"r"(bar), "r"(bytes) : "memory");
}
__device__ __forceinline__ void mbar_arrive(uint32_t bar) {
    asm volatile("mbarrier.arrive.shared::cta.b64 _, [%0];" ::"r"(bar) : "memory");
}
__device__ __forceinline__ void mbar_wait(uint32_t bar, uint32_t parity = 0) {
    asm volatile(
        "{\n.reg .pred p;\n.reg .u32 c;\nmov.u32 c, 0;\n"
        "WAIT_LOOP:\nmbarrier.try_wait.parity.shared::cta.b64 p, [%0], %2;\n@p bra WAIT_DONE;\n"
        "add.u32 c, c, 1;\nsetp.lt.u32 p, c, %1;\n@p bra WAIT_LOOP;\ntrap;\nWAIT_DONE:\n}"
        ::"r"(bar), "n"(SPIN_LIMIT), "r"(parity) : "memory");
}
__device__ __forceinline__ bool bar_or(int id, int n, bool v) {
    uint32_t r;
    asm volatile("{\n.reg .pred p, q;\nsetp.ne.u32 q, %3, 0;\nbar.red.or.pred p, %1, %2, q;\nselp.u32 %0, 1, 0, p;\n}"
                 : "=r"(r) : "r"(id), "r"(n), "r"((uint32_t)v) : "memory");
    return __any_sync(~0u, r);
}
__device__ __forceinline__ void bar_sync(int id, int n) { asm volatile("bar.sync %0, %1;" ::"r"(id), "r"(n) : "memory"); }
__device__ __forceinline__ void fence_async_smem() { asm volatile("fence.proxy.async.shared::cta;" ::: "memory"); }
__device__ __forceinline__ void tma3(uint32_t dst, const CUtensorMap* m, int c0, int c1, int c2, uint32_t bar, uint64_t pol) {
    asm volatile(
        "cp.async.bulk.tensor.3d.shared::cluster.global.mbarrier::complete_tx::bytes.L2::cache_hint [%0], [%1, {%2, %3, %4}], [%5], %6;"
        ::"r"(dst), "l"(m), "r"(c0), "r"(c1), "r"(c2), "r"(bar), "l"(pol) : "memory");
}
__device__ __forceinline__ void bulk_load(uint32_t dst, const void* src, uint32_t bytes, uint32_t bar) {
    asm volatile("cp.async.bulk.shared::cluster.global.mbarrier::complete_tx::bytes [%0], [%1], %2, [%3];"
                 ::"r"(dst), "l"(src), "r"(bytes), "r"(bar) : "memory");
}
__device__ __forceinline__ uint32_t lds_u32(uint32_t a) { uint32_t v; asm volatile("ld.shared.u32 %0, [%1];" : "=r"(v) : "r"(a) : "memory"); return v; }
__device__ __forceinline__ float lds_bf(uint32_t a) {
    unsigned short v;
    asm volatile("ld.shared.u16 %0, [%1];" : "=h"(v) : "r"(a) : "memory");
    return __uint_as_float((uint32_t)v << 16);
}
__device__ __forceinline__ uint4 ld_x(const uint4* p) {
    uint4 v;
    asm volatile("{\n.reg .b64 a, b;\nld.relaxed.gpu.global.v2.b64 {a, b}, [%4];\nmov.b64 {%0,%1}, a;\nmov.b64 {%2,%3}, b;\n}"
                 : "=r"(v.x), "=r"(v.y), "=r"(v.z), "=r"(v.w) : "l"(p) : "memory");
    return v;
}
__device__ __forceinline__ void st_x(uint4* p, uint4 v) {
    asm volatile("{\n.reg .b64 a, b;\nmov.b64 a, {%1,%2};\nmov.b64 b, {%3,%4};\nst.relaxed.gpu.global.v2.b64 [%0], {a, b};\n}"
                 ::"l"(p), "r"(v.x), "r"(v.y), "r"(v.z), "r"(v.w) : "memory");
}
__device__ __forceinline__ uint2 ld_x64(const uint2* p) {
    uint2 v;
    asm volatile("{\n.reg .b64 a;\nld.relaxed.gpu.global.b64 a, [%2];\nmov.b64 {%0,%1}, a;\n}" : "=r"(v.x), "=r"(v.y) : "l"(p) : "memory");
    return v;
}
__device__ __forceinline__ void st_x64(uint2* p, uint2 v) {
    asm volatile("{\n.reg .b64 a;\nmov.b64 a, {%1,%2};\nst.relaxed.gpu.global.b64 [%0], a;\n}" ::"l"(p), "r"(v.x), "r"(v.y) : "memory");
}
__device__ __forceinline__ uint32_t ld_x32(const uint32_t* p) {
    uint32_t v;
    asm volatile("ld.relaxed.gpu.global.u32 %0, [%1];" : "=r"(v) : "l"(p) : "memory");
    return v;
}
__device__ __forceinline__ void st_x32(uint32_t* p, uint32_t v) { asm volatile("st.relaxed.gpu.global.u32 [%0], %1;" ::"l"(p), "r"(v) : "memory"); }
template <uint32_t MASK>
__device__ __forceinline__ uint32_t set_tag(uint32_t w, uint32_t tag) {
    uint32_t r;
    asm("lop3.b32 %0, %1, %2, %3, 0xEA;" : "=r"(r) : "r"(w), "n"(~MASK), "r"(tag));
    return r;
}
__device__ __forceinline__ uint32_t tag_bad(uint4 v, uint32_t tag) {
    uint32_t r;
    asm("lop3.b32 %0, %1, %2, %3, 0x7E;" : "=r"(r) : "r"(v.x), "r"(v.z), "r"(tag));
    return r;
}
__device__ __forceinline__ uint4 tag4(float a, float b, float c, float d, uint32_t tag) {
    return make_uint4(set_tag<3>(__float_as_uint(a), tag), __float_as_uint(b), set_tag<3>(__float_as_uint(c), tag), __float_as_uint(d));
}
__device__ __forceinline__ void red_add1(uint32_t* p) { asm volatile("red.relaxed.gpu.global.add.u32 [%0], 1;" ::"l"(p) : "memory"); }
__device__ __forceinline__ uint32_t next_epoch(uint32_t e) { asm volatile("add.u32 %0, %0, 1;" : "+r"(e)::"memory"); return e; }
__device__ __forceinline__ void spin_check(int& it) {
    if (++it > SPIN_LIMIT) asm volatile("trap;");
}
__device__ __forceinline__ float lds_f(uint32_t a) { float v; asm volatile("ld.shared.f32 %0, [%1];" : "=f"(v) : "r"(a) : "memory"); return v; }
__device__ __forceinline__ float4 lds_f4(uint32_t a) {
    float4 v;
    asm volatile("ld.shared.v4.f32 {%0,%1,%2,%3}, [%4];" : "=f"(v.x), "=f"(v.y), "=f"(v.z), "=f"(v.w) : "r"(a) : "memory");
    return v;
}
__device__ __forceinline__ uint4 lds_u4(uint32_t a) {
    uint4 v;
    asm volatile("ld.shared.v4.u32 {%0,%1,%2,%3}, [%4];" : "=r"(v.x), "=r"(v.y), "=r"(v.z), "=r"(v.w) : "r"(a) : "memory");
    return v;
}
__device__ __forceinline__ void sts_f(uint32_t a, float v) { asm volatile("st.shared.f32 [%0], %1;" ::"r"(a), "f"(v) : "memory"); }
__device__ __forceinline__ void sts_u16(uint32_t a, uint32_t v) { asm volatile("st.shared.u16 [%0], %1;" ::"r"(a), "h"((unsigned short)v) : "memory"); }
__device__ __forceinline__ void sts_u2(uint32_t a, uint32_t x, uint32_t y) { asm volatile("st.shared.v2.u32 [%0], {%1,%2};" ::"r"(a), "r"(x), "r"(y) : "memory"); }
__device__ __forceinline__ void sts_u4(uint32_t a, uint4 v) {
    asm volatile("st.shared.v4.u32 [%0], {%1,%2,%3,%4};" ::"r"(a), "r"(v.x), "r"(v.y), "r"(v.z), "r"(v.w) : "memory");
}
__device__ __forceinline__ void sts_f4(uint32_t a, float x, float y, float z, float w) {
    asm volatile("st.shared.v4.f32 [%0], {%1,%2,%3,%4};" ::"r"(a), "f"(x), "f"(y), "f"(z), "f"(w) : "memory");
}
__device__ __forceinline__ float2 lds_f2(uint32_t a) {
    float2 v;
    asm volatile("ld.shared.v2.f32 {%0,%1}, [%2];" : "=f"(v.x), "=f"(v.y) : "r"(a) : "memory");
    return v;
}
__device__ __forceinline__ void cp_async16(uint32_t dst, const void* src) {
    asm volatile("cp.async.cg.shared.global [%0], [%1], 16;" ::"r"(dst), "l"(src) : "memory");
}
__device__ __forceinline__ uint64_t gtime() { uint64_t t; asm volatile("mov.u64 %0, %%globaltimer;" : "=l"(t)); return t; }
__device__ __forceinline__ uint32_t map_peer(uint32_t addr, int rank) {
    uint32_t r;
    asm("mapa.shared::cluster.u32 %0, %1, %2;" : "=r"(r) : "r"(addr), "r"(rank));
    return r;
}
__device__ __forceinline__ void st_peer4(uint32_t addr, uint32_t a, uint32_t b, uint32_t c, uint32_t d, uint32_t bar) {
    asm volatile("st.async.weak.shared::cluster.mbarrier::complete_tx::bytes.v4.b32 [%0], {%1,%2,%3,%4}, [%5];"
                 ::"r"(addr), "r"(a), "r"(b), "r"(c), "r"(d), "r"(bar) : "memory");
}
__device__ __forceinline__ void st_peer1(uint32_t addr, float a, uint32_t bar) {
    asm volatile("st.async.weak.shared::cluster.mbarrier::complete_tx::bytes.f32 [%0], %1, [%2];" ::"r"(addr), "f"(a), "r"(bar) : "memory");
}
__device__ __forceinline__ void cluster_arrive() { asm volatile("barrier.cluster.arrive.relaxed.aligned;" ::: "memory"); }
__device__ __forceinline__ void cluster_wait() { asm volatile("barrier.cluster.wait.acquire.aligned;" ::: "memory"); }
__device__ __forceinline__ void bar_arrive(int id, int n) { asm volatile("bar.arrive %0, %1;" ::"r"(id), "r"(n) : "memory"); }
__device__ __forceinline__ float rcp_fast(float x) { float r; asm("rcp.approx.ftz.f32 %0, %1;" : "=f"(r) : "f"(x)); return r; }
__device__ __forceinline__ float rsq_fast(float x) { float r; asm("rsqrt.approx.ftz.f32 %0, %1;" : "=f"(r) : "f"(x)); return r; }
__device__ __forceinline__ float ldg_bf(const __nv_bfloat16* p) {
    unsigned short v;
    asm volatile("ld.global.nc.u16 %0, [%1];" : "=h"(v) : "l"(p));
    return __uint_as_float((uint32_t)v << 16);
}
__device__ __forceinline__ float max4(float4 v) { return fmaxf(fmaxf(v.x, v.y), fmaxf(v.z, v.w)); }
__device__ __forceinline__ float sum4(float4 v) { return (v.x + v.y) + (v.z + v.w); }
__device__ __forceinline__ uint32_t pack_bf16(float lo, float hi) {
    uint32_t r;
    asm("cvt.rn.bf16x2.f32 %0, %1, %2;" : "=r"(r) : "f"(hi), "f"(lo));
    return r;
}
__device__ __forceinline__ uint32_t split_bf16(float v) { return pack_bf16(v, v - __uint_as_float(pack_bf16(v, v) << 16)); }
__device__ __forceinline__ float bf_lo(uint32_t w) { return __uint_as_float(w << 16); }
__device__ __forceinline__ float bf_hi(uint32_t w) { return __uint_as_float(w & 0xFFFF0000u); }
__device__ __forceinline__ float ex2(float x) { float r; asm("ex2.approx.ftz.f32 %0, %1;" : "=f"(r) : "f"(x)); return r; }
__device__ __forceinline__ float tanh_fast(float x) { float r; asm("tanh.approx.f32 %0, %1;" : "=f"(r) : "f"(x)); return r; }
__device__ __forceinline__ void mma16816(float (&c)[4], uint32_t a0, uint32_t a1, uint32_t a2, uint32_t a3, uint32_t b0, uint32_t b1) {
    asm volatile("mma.sync.aligned.m16n8k16.row.col.f32.bf16.bf16.f32 {%0,%1,%2,%3}, {%4,%5,%6,%7}, {%8,%9}, {%0,%1,%2,%3};"
                 : "+f"(c[0]), "+f"(c[1]), "+f"(c[2]), "+f"(c[3]) : "r"(a0), "r"(a1), "r"(a2), "r"(a3), "r"(b0), "r"(b1));
}
__device__ __forceinline__ uint4 ldsm4(uint32_t a) {
    uint4 v;
    asm volatile("ldmatrix.sync.aligned.m8n8.x4.shared.b16 {%0,%1,%2,%3}, [%4];" : "=r"(v.x), "=r"(v.y), "=r"(v.z), "=r"(v.w) : "r"(a) : "memory");
    return v;
}
__device__ __forceinline__ uint4 ldsm4t(uint32_t a) {
    uint4 v;
    asm volatile("ldmatrix.sync.aligned.m8n8.x4.trans.shared.b16 {%0,%1,%2,%3}, [%4];" : "=r"(v.x), "=r"(v.y), "=r"(v.z), "=r"(v.w) : "r"(a) : "memory");
    return v;
}
__device__ __forceinline__ void stsm4t(uint32_t a, uint32_t r0, uint32_t r1, uint32_t r2, uint32_t r3) {
    asm volatile("stmatrix.sync.aligned.m8n8.x4.trans.shared.b16 [%0], {%1,%2,%3,%4};" ::"r"(a), "r"(r0), "r"(r1), "r"(r2), "r"(r3) : "memory");
}
__device__ __forceinline__ void stsm2t(uint32_t a, uint32_t r0, uint32_t r1) {
    asm volatile("stmatrix.sync.aligned.m8n8.x2.trans.shared.b16 [%0], {%1,%2};" ::"r"(a), "r"(r0), "r"(r1) : "memory");
}
__device__ __forceinline__ uint32_t make_desc(uint32_t addr) { return (addr >> 4) | (1u << 16); }
__device__ __forceinline__ void wg_fence() { asm volatile("wgmma.fence.sync.aligned;" ::: "memory"); }
__device__ __forceinline__ void wg_commit() { asm volatile("wgmma.commit_group.sync.aligned;" ::: "memory"); }
template <int N>
__device__ __forceinline__ void wg_wait() { asm volatile("wgmma.wait_group.sync.aligned %0;" ::"n"(N) : "memory"); }
template <int TA>
__device__ __forceinline__ void wgmma32(float (&d)[16], uint32_t da, uint32_t db) {
    asm volatile(
        "{\n.reg .b64 a, b;\nmov.b64 a, {%16, 0x40000040};\nmov.b64 b, {%17, 0x40000040};\n"
        "wgmma.mma_async.sync.aligned.m64n32k16.f32.bf16.bf16 "
        "{%0,%1,%2,%3,%4,%5,%6,%7,%8,%9,%10,%11,%12,%13,%14,%15}, a, b, 1, 1, 1, %18, 0;\n}\n"
        : "+f"(d[0]), "+f"(d[1]), "+f"(d[2]), "+f"(d[3]), "+f"(d[4]), "+f"(d[5]), "+f"(d[6]), "+f"(d[7]),
          "+f"(d[8]), "+f"(d[9]), "+f"(d[10]), "+f"(d[11]), "+f"(d[12]), "+f"(d[13]), "+f"(d[14]), "+f"(d[15])
        : "r"(da), "r"(db), "n"(TA));
}
__device__ __forceinline__ void reg_fence(float (&d)[16]) {
#pragma unroll
    for (int i = 0; i < 16; i++) asm volatile("" : "+f"(d[i])::"memory");
}
template <bool MAX>
__device__ __forceinline__ float reduce8(const float (&v)[8], int lane) {
    float a[4], b[2];
    const bool h4 = lane & 16, h2 = lane & 8, h1 = lane & 4;
#pragma unroll
    for (int i = 0; i < 4; i++) {
        float keep = h4 ? v[i + 4] : v[i], send = h4 ? v[i] : v[i + 4];
        float r = __shfl_xor_sync(~0u, send, 16);
        a[i] = MAX ? fmaxf(keep, r) : keep + r;
    }
#pragma unroll
    for (int i = 0; i < 2; i++) {
        float keep = h2 ? a[i + 2] : a[i], send = h2 ? a[i] : a[i + 2];
        float r = __shfl_xor_sync(~0u, send, 8);
        b[i] = MAX ? fmaxf(keep, r) : keep + r;
    }
    float keep = h1 ? b[1] : b[0], send = h1 ? b[0] : b[1];
    float r = __shfl_xor_sync(~0u, send, 4);
    return MAX ? fmaxf(keep, r) : keep + r;
}

struct Params {
    const __nv_bfloat16 *x, *w1, *b1, *w2, *b2, *gate_w;
    __nv_bfloat16* out;
    Scratch* s;
};

__device__ __forceinline__ void rescale(float (&o)[4][16], uint32_t mxa, int t) {
    const float m0 = max4(lds_f4(mxa));
    const float al = ex2(m0 - fmaxf(m0, max4(lds_f4(mxa + 512))));
#pragma unroll
    for (int jj = 0; jj < 4; jj++) {
        const float a0 = __shfl_sync(~0u, al, 8 * jj + t), a1 = __shfl_sync(~0u, al, 8 * jj + 4 + t);
#pragma unroll
        for (int i = 0; i < 4; i++) {
            o[i][4 * jj] *= a0; o[i][4 * jj + 1] *= a1;
            o[i][4 * jj + 2] *= a0; o[i][4 * jj + 3] *= a1;
        }
    }
}

__device__ __forceinline__ uint32_t ord_flip(uint32_t i) { return i ^ (((int)i >> 31) & 0x7FFFFFFF); }

__device__ __forceinline__ void wait_count1(const uint32_t* p, uint32_t v, uint32_t want, int& it) {
#pragma unroll 1
    while (v != want) {
        v = ld_x32(p);
        spin_check(it);
    }
}

__device__ __forceinline__ uint32_t frag_off(int b, int k) {
    return (k >> 5) * 256 + b * 64 + ((k >> 1) & 3) * 16 + ((k >> 3) & 3) * 4 + (k & 1) * 2;
}

template <int NK, bool FRAG>
__device__ __forceinline__ void gemv_publish(const uint4 (&a)[NK], uint32_t bbase, uint4* dst, uint32_t own, int t, uint32_t tag2) {
    uint4 bv[(NK + 1) / 2];
#pragma unroll
    for (int k2 = 0; k2 < (NK + 1) / 2; k2++) bv[k2] = FRAG ? lds_u4(bbase + k2 * 256) : ldsm4(bbase + k2 * 64);
    float c[4][4] = {};
#pragma unroll
    for (int k = 0; k < NK; k++)
        mma16816(c[k & 3], a[k].x, a[k].y, a[k].z, a[k].w, (k & 1) ? bv[k >> 1].z : bv[k >> 1].x, (k & 1) ? bv[k >> 1].w : bv[k >> 1].y);
    if (t < 2) {
        const uint4 v = tag4((c[0][0] + c[1][0]) + (c[2][0] + c[3][0]), (c[0][1] + c[1][1]) + (c[2][1] + c[3][1]),
                             (c[0][2] + c[1][2]) + (c[2][2] + c[3][2]), (c[0][3] + c[1][3]) + (c[2][3] + c[3][3]), tag2);
        st_x(dst, v);
        sts_u4(own, v);
    }
    __syncwarp();
}

template <class F>
__device__ __forceinline__ void gather_sum(uint32_t sb, const uint4* src, int j, int ww, int lane, uint32_t tag2, int& it, int slot, F&& overlap) {
    const int g = lane >> 2, t = lane & 3;
    uint4 x[2];
    if (t != j) {
        x[0] = ld_x(src);
        x[1] = ld_x(src + 8);
    } else {
        x[0] = lds_u4(sb + OFF_STAGE + ww * 256 + g * 16);
        x[1] = lds_u4(sb + OFF_STAGE + ww * 256 + g * 16 + 128);
    }
    overlap();
#pragma unroll 1
    while (__any_sync(~0u, (tag_bad(x[0], tag2) | tag_bad(x[1], tag2)) & 3)) {
        if (t != j) {
            x[0] = ld_x(src);
            x[1] = ld_x(src + 8);
        }
        spin_check(it);
    }
    const bool hi = t & 2, od = t & 1;
#pragma unroll
    for (int i = 0; i < 2; i++) {
        const float a0 = __uint_as_float(hi ? x[i].z : x[i].x) + __shfl_xor_sync(~0u, __uint_as_float(hi ? x[i].x : x[i].z), 2);
        const float a1 = __uint_as_float(hi ? x[i].w : x[i].y) + __shfl_xor_sync(~0u, __uint_as_float(hi ? x[i].y : x[i].w), 2);
        const float r = (od ? a1 : a0) + __shfl_xor_sync(~0u, od ? a0 : a1, 1);
        sts_u16(sb + OFF_QS + frag_off(2 * (g & 1) + (t & 1), 16 * ww + 4 * i + (g >> 1) + 8 * (t >> 1)), pack_bf16(r, r));
    }
}

struct OutTile {
    uint4 a[8];
    float y[4], gate0, gate1;
    uint32_t abase, dst;
    __device__ __forceinline__ void setup(uint32_t sb, int cta, int mt, int lane) {
        const int g = lane >> 2, t = lane & 3, lq = lane >> 3, li = lane & 7;
        const uint32_t ya = sb + OFF_Y + (2 * (t & 1) * MQ + 16 * mt + g) * 4;
#pragma unroll
        for (int i = 0; i < 4; i++) {
            const uint32_t q = ya + (i & 1) * (MQ * 4) + (i >> 1) * 32;
            y[i] = lds_f(q) + lds_f(q + 4 * MQ * 4);
        }
        gate0 = lds_f(sb + OFF_GATE + (t & 1) * 8);
        gate1 = lds_f(sb + OFF_GATE + (t & 1) * 8 + 4);
        abase = sb + OFF_C + (8 * (lq >> 1) + li) * WOP + 32 * mt + 16 * (lq & 1);
        dst = (((cta & 3) * 18 + 2 * mt + (g >> 2)) * NH + (cta >> 2)) * 8 + 2 * (g & 3) + t;
        asm volatile("" : "+r"(dst), "+r"(abase));
    }
    __device__ __forceinline__ void prefetch(uint32_t sb) {
        mbar_wait(sb + OFF_BAR + 8 * BAR_WO);
#pragma unroll
        for (int k = 0; k < 8; k++) a[k] = ldsm4t(abase + k * (16 * WOP));
    }
    __device__ __forceinline__ void finish(uint32_t sb, Scratch* s, int mt, int lane, uint32_t tag2 TLARG) {
        bar_sync(7, 288);
        if (mt == 0 && lane == 0) TL(45);
        const uint32_t bbase = sb + OFF_QS + ((lane >> 2) & 3) * 64 + (lane & 3) * 16;
        uint4 bv[4];
#pragma unroll
        for (int k2 = 0; k2 < 4; k2++) bv[k2] = lds_u4(bbase + k2 * 256);
        float c0[4] = {}, c1[4] = {}, c2[4] = {}, c3[4] = {};
#pragma unroll
        for (int k2 = 0; k2 < 2; k2++) {
            mma16816(c0, a[2 * k2].x, a[2 * k2].y, a[2 * k2].z, a[2 * k2].w, bv[k2].x, bv[k2].y);
            mma16816(c1, a[2 * k2 + 1].x, a[2 * k2 + 1].y, a[2 * k2 + 1].z, a[2 * k2 + 1].w, bv[k2].z, bv[k2].w);
            mma16816(c2, a[2 * k2 + 4].x, a[2 * k2 + 4].y, a[2 * k2 + 4].z, a[2 * k2 + 4].w, bv[k2 + 2].x, bv[k2 + 2].y);
            mma16816(c3, a[2 * k2 + 5].x, a[2 * k2 + 5].y, a[2 * k2 + 5].z, a[2 * k2 + 5].w, bv[k2 + 2].z, bv[k2 + 2].w);
        }
#pragma unroll
        for (int e = 0; e < 4; e++) {
            c0[e] += c2[e];
            c1[e] += c3[e];
        }
        if ((lane & 3) < 2)
            st_x(&s->e5[dst], tag4(fmaf(c0[0] + c1[0], gate0, y[0]), fmaf(c0[1] + c1[1], gate1, y[1]),
                           fmaf(c0[2] + c1[2], gate0, y[2]), fmaf(c0[3] + c1[3], gate1, y[3]), tag2));
    }
};

__global__ void __cluster_dims__(2, 1, 1) __launch_bounds__(NTHREADS, 1)
fused_decode_kernel(const Params p, const __grid_constant__ CUtensorMap map_q, const __grid_constant__ CUtensorMap map_uk,
                    const __grid_constant__ CUtensorMap map_c, const __grid_constant__ CUtensorMap map_uv,
                    const __grid_constant__ CUtensorMap map_o) {
    extern __shared__ __align__(1024) uint8_t smem_raw[];
    const uint32_t sb = smem_u32(smem_raw);
    const int tid = (SWAP && threadIdx.x < 512) ? (threadIdx.x ^ 256) : threadIdx.x;
    const int lane = tid & 31, g = lane >> 2, t = lane & 3;
    const int warp = __shfl_sync(~0u, tid >> 5, 0);
    const int cta = blockIdx.x, h = cta >> 2, j = cta & 3;
    const int rank = cta & 1;
    const uint32_t bars = sb + OFF_BAR;

    if (warp < 8) {
        const int wg = warp >> 2, w = warp & 3;
        const int b = cta >> 5;
        {
            const int i2 = tid + 256;
            const __nv_bfloat16* s2 = i2 < 288 ? p.x + i2 * 8 : i2 < 360 ? p.gate_w + (i2 - 288) * 8
                                    : i2 < 378 ? p.w1 + h * FPH + (i2 - 360) * 8
                                    : i2 < 396 ? p.b1 + h * FPH + (i2 - 378) * 8 : p.w2 + h * FPH + (i2 - 396) * 8;
            cp_async16(sb + OFF_X + tid * 16, p.x + tid * 8);
            if (i2 < 414) cp_async16(sb + OFF_X + i2 * 16, s2);
            if (tid >= 224) sts_f4(sb + OFF_MX + 512 + (tid - 224) * 16, -INFINITY, -INFINITY, -INFINITY, -INFINITY);
        }
        asm volatile("setmaxnreg.inc.sync.aligned.u32 %0;" ::"n"(REG_A));
        asm volatile("cp.async.wait_all;" ::: "memory");
        bar_sync(6, NSTART);
        cluster_arrive();
        if (tid == 0) TL(18);
        {
            const uint32_t xa = sb + OFF_X + (warp >> 1) * (DM * 2);
            const int m0 = (warp & 1) * 32 + lane;
            const float x0 = lds_bf(xa);
            float s1 = 0.f, s2 = 0.f, d = 0.f;
#pragma unroll
            for (int i = 0; i < 9; i++) {
                const float xv = lds_bf(xa + m0 * 2 + 128 * i);
                d = fmaf(xv, lds_bf(sb + OFF_GW + m0 * 2 + 128 * i), d);
                s1 += xv - x0;
                s2 = fmaf(xv - x0, xv - x0, s2);
            }
#pragma unroll
            for (int o = 16; o; o >>= 1) {
                s1 += __shfl_xor_sync(~0u, s1, o);
                s2 += __shfl_xor_sync(~0u, s2, o);
                d += __shfl_xor_sync(~0u, d, o);
            }
            if (lane == 0) sts_f4(sb + OFF_STAT + warp * 16, s1, s2, d, 0.f);
            if (tid == 0) TL(49);
            bar_sync(2, 256);
            const float4 pa = lds_f4(sb + OFF_STAT + (warp >> 1) * 32), pb = lds_f4(sb + OFF_STAT + (warp >> 1) * 32 + 16);
            const float mean = (pa.x + pb.x) * (1.f / DM);
            const float rstd = rsq_fast(fmaxf(fmaf(-mean, mean, (pa.y + pb.y) * (1.f / DM)), 0.f) + 1e-5f);
            const float gate = rcp_fast(1.f + ex2(-1.4426950408889634f * (pa.z + pb.z)));
            if (lane == 0) sts_f(sb + OFF_GATE + (warp >> 1) * 4, gate);
#pragma unroll 1
            for (int r = m0; r < MQ; r += 64) {
                const float hh = (lds_bf(xa + (MQ * j + r) * 2) - x0 - mean) * rstd;
                sts_u4(sb + OFF_MA + ((warp >> 1) * MQ + r) * 16, make_uint4(0x3F80u, split_bf16(hh), split_bf16(hh * hh), split_bf16(hh * hh * hh)));
            }
            fence_async_smem();
            bar_sync(5, 416);
            if (tid == 0) { TL(51); }
            uint4 ra[9];
            float acc[9][2];
#pragma unroll
            for (int i = 0; i < 9; i++) {
                ra[i] = ldsm4(sb + OFF_MA + ((warp >> 1) * MQ + 16 * i + (lane & 15)) * 16);
                acc[i][0] = acc[i][1] = 0.f;
            }
            if (lane == 0) mbar_arrive(bars + 8 * BAR_WKFREE);
            uint32_t ba = sb + OFF_MB + ((warp & 1) * 72 + g) * 64 + t * 16;
            uint4 bn = lds_u4(ba);
            float ksum = 0.f;
#pragma unroll 1
            for (int nt = 0; nt < NTMAX; nt++) {
                const uint4 bv = bn;
                ba += 512;
                bn = lds_u4(ba);
                ksum += bf_lo(bv.z) + bf_lo(bv.w);
#pragma unroll
                for (int i = 0; i < 9; i++) {
                    float u[4] = {}, av[4] = {};
                    mma16816(u, ra[i].x, ra[i].y, ra[i].z, ra[i].w, bv.x, bv.y);
                    mma16816(av, ra[i].x, ra[i].y, ra[i].z, ra[i].w, bv.z, bv.w);
                    acc[i][0] = fmaf(av[0], tanh_fast(u[0]), fmaf(av[1], tanh_fast(u[1]), acc[i][0]));
                    acc[i][1] = fmaf(av[2], tanh_fast(u[2]), fmaf(av[3], tanh_fast(u[3]), acc[i][1]));
                }
            }
            if (tid == 0) { TL(52); }
            ksum += __shfl_xor_sync(~0u, ksum, 4);
            ksum += __shfl_xor_sync(~0u, ksum, 8);
            ksum += __shfl_xor_sync(~0u, ksum, 16);
            const uint32_t ks = split_bf16(0.25f * ksum);
            const uint32_t kb0 = __byte_perm(ks, 0, 0x1010), kb1 = __byte_perm(ks, 0, 0x3232);
            const uint32_t ya = sb + OFF_Y + (((warp & 1) * 4 + (warp >> 1)) * MQ + g + 8 * (t >> 1)) * 4;
#pragma unroll
            for (int i = 0; i < 9; i++) {
                float lin[4] = {};
                mma16816(lin, ra[i].x, ra[i].y, ra[i].z, ra[i].w, kb0, kb1);
                const float v0 = acc[i][0] + lin[0], v1 = acc[i][1] + lin[2];
                const float y = ((t & 2) ? v1 : v0) + __shfl_xor_sync(~0u, (t & 2) ? v0 : v1, 2);
                const float yy = (y + __shfl_xor_sync(~0u, y, 1)) * (1.f - gate);
                if ((t & 1) == 0) sts_f(ya + 64 * i, yy);
            }
        }
        if (tid == 0) TL(12);

        cluster_wait();
        mbar_wait(bars + 8 * BAR_Q);
        if (tid == 0) TL(13);
        const uint32_t epoch = lds_u32(sb + OFF_EPOCH), tag = epoch & 1;
        {
            int it = 0;
#pragma unroll 1
            for (uint32_t par = 1;; par ^= 1) {
                uint32_t bad = 0;
#pragma unroll
                for (int i = 0; i < 8; i++) bad |= tag_bad(lds_u4(sb + OFF_Q + tid * 16 + i * 4096), tag);
                if (!bar_or(2, 256, bad & 1)) break;
                if (tid == 0) {
                    mbar_expect_tx(bars + 8 * BAR_Q, 32768);
                    bulk_load(sb + OFF_Q, &p.s->e2[(rank * 4 + b) * 2048], 32768, bars + 8 * BAR_Q);
                }
                mbar_wait(bars + 8 * BAR_Q, par);
                spin_check(it);
            }
        }
        if (tid == 0) { TL(14); }

        float o[4][16];
#pragma unroll
        for (int i = 0; i < 4; i++)
#pragma unroll
            for (int k = 0; k < 16; k++) o[i][k] = 0.f;
        const uint32_t mxa = sb + OFF_MX + (8 * (g >> 1) + 2 * t + (g & 1)) * 16;
#pragma unroll 1
        for (int s = 0; s < 2; s++) {
            float v[8] = {};
            if (wg == s) {
                float sc[16];
#pragma unroll
                for (int k = 0; k < 16; k++) sc[k] = 0.f;
                uint32_t da = make_desc(sb + OFF_C + s * 65536), db = make_desc(sb + OFF_Q);
#pragma unroll 1
                for (int q = 0; q < 4; q++) {
                    mbar_wait(bars + 8 * (BAR_C + 4 * s + q));
                    wg_fence();
#pragma unroll
                    for (int k = 0; k < 8; k++)
                        wgmma32<0>(sc, da + (((k >> 2) * 8192 + (k & 3) * 32) >> 4), db + (((k >> 2) * 4096 + (k & 3) * 32) >> 4));
                    wg_commit();
                    da += 16384 >> 4;
                    db += 8192 >> 4;
                }
                if (s == 1) mbar_wait(bars + 8 * BAR_PF);
                const float mold = max4(lds_f4(mxa + 512 - 512 * s));
                float mr[8];
#pragma unroll
                for (int i = 0; i < 8; i++) mr[i] = __shfl_sync(~0u, mold, 4 * i + t);
                const int q = lane >> 3, i = lane & 7;
                const uint32_t pa = sb + OFF_P + s * 4096 + (8 * (q >> 1) + i) * 128 + (((2 * w + (q & 1)) ^ i) << 4);
                wg_wait<0>();
                reg_fence(sc);
                if (tid == 128 * s) TL(15 + 4 * s);
                bool exact = s == 0;
#pragma unroll 1
                for (;;) {
                    if (exact) {
#pragma unroll
                        for (int n = 0; n < 8; n++) v[n] = fmaxf(sc[4 * (n >> 1) + (n & 1)], sc[4 * (n >> 1) + 2 + (n & 1)]);
                        sts_f(mxa + s * 512 + w * 4, reduce8<true>(v, lane));
                        bar_sync(3, 128 << s);
                        const float mnew = fmaxf(mold, max4(lds_f4(mxa + s * 512)));
#pragma unroll
                        for (int n = 0; n < 8; n++) mr[n] = __shfl_sync(~0u, mnew, 4 * n + t);
                        if (s == 1) rescale(o, mxa, t);
                    }
                    uint32_t pk[8];
#pragma unroll
                    for (int jj = 0; jj < 4; jj++) {
                        const float p0 = ex2(sc[4 * jj] - mr[2 * jj]), p1 = ex2(sc[4 * jj + 1] - mr[2 * jj + 1]);
                        const float p2 = ex2(sc[4 * jj + 2] - mr[2 * jj]), p3 = ex2(sc[4 * jj + 3] - mr[2 * jj + 1]);
                        pk[2 * jj] = pack_bf16(p0, p1);
                        pk[2 * jj + 1] = pack_bf16(p2, p3);
                        v[2 * jj] = p0 + p2;
                        v[2 * jj + 1] = p1 + p3;
                    }
                    stsm4t(pa, pk[0], pk[1], pk[2], pk[3]);
                    stsm4t(pa + 2048, pk[4], pk[5], pk[6], pk[7]);
                    fence_async_smem();
                    const float tot = ((v[0] + v[1]) + (v[2] + v[3])) + ((v[4] + v[5]) + (v[6] + v[7]));
                    if (!bar_or(2, 256, !exact && !(tot <= LAZY_LIMIT))) break;
                    exact = true;
                }
            } else {
                if (s == 1) mbar_wait(bars + 8 * BAR_PF);
#pragma unroll 1
                while (bar_or(2, 256, false)) {
                    bar_sync(3, 256);
                    rescale(o, mxa, t);
                }
            }
            if (tid == 0) { TL(16 + 4 * s); TLG(59); }
            if (s == 1 && tid == 0) mbar_arrive(bars + 8 * BAR_LATE);
            wg_fence();
#pragma unroll
            for (int hp = 0; hp < 2; hp++) {
                const uint32_t da = make_desc(sb + OFF_C + s * 65536 + wg * 32768 + hp * 16384), db = make_desc(sb + OFF_P + s * 4096);
#pragma unroll
                for (int k = 0; k < 4; k++) {
                    wgmma32<1>(o[2 * hp], da + ((k * 2048) >> 4), db + ((k * 32) >> 4));
                    wgmma32<1>(o[2 * hp + 1], da + ((8192 + k * 2048) >> 4), db + ((k * 32) >> 4));
                }
                wg_commit();
            }
            if (s == 0) {
                if (wg == 0) sts_f(mxa + 1024 + w * 4, reduce8<false>(v, lane));
                wg_wait<0>();
#pragma unroll
                for (int i = 0; i < 4; i++) reg_fence(o[i]);
                if (lane == 0) {
                    mbar_arrive(bars + 8 * BAR_C0FREE);
                    asm volatile("mbarrier.arrive.relaxed.cluster.shared::cluster.b64 _, [%0];" ::"r"(map_peer(bars + 8 * BAR_PF, rank ^ 1)) : "memory");
                }
                if (tid == 0) TL(17);
            } else {
                int lv = lane;
                asm volatile("" : "+r"(lv));
                const int pr = (cta >> 1) & 15;
                uint2* dst = reinterpret_cast<uint2*>(&p.s->e3[((16 * rank + 2 * (lv & 3)) * 4 + 2 * wg + (w >> 1)) * 1024 + (b * 16 + pr) * 8]) + (w & 1) * 8 + (lv >> 2);
                uint32_t* cnt = &p.s->c3[((b * 2 + rank) * 8 + 4 * wg + 2 * (w >> 1)) * 32];
                const uint32_t pd = map_peer(sb + OFF_PD + tid * 16, rank ^ 1), pbar = map_peer(bars + 8 * BAR_PD, rank ^ 1);
#pragma unroll
                for (int hp = 0; hp < 2; hp++) {
                    if (hp == 0) wg_wait<1>(); else wg_wait<0>();
                    reg_fence(o[2 * hp]);
                    reg_fence(o[2 * hp + 1]);
                    TLM(hp ? 21 : 37);
                    uint32_t sw[8];
#pragma unroll
                    for (int n = 0; n < 4; n++) {
                        const int a = 4 * (n >> 1) + (n & 1);
                        sw[2 * n] = pack_bf16(o[2 * hp][a + 8], o[2 * hp][a + 10]);
                        sw[2 * n + 1] = pack_bf16(o[2 * hp + 1][a + 8], o[2 * hp + 1][a + 10]);
                    }
                    st_peer4(pd + hp * 8192, sw[0], sw[1], sw[2], sw[3], pbar + hp * 8);
                    st_peer4(pd + hp * 8192 + 4096, sw[4], sw[5], sw[6], sw[7], pbar + hp * 8);
                }
                TLM(5);
                if (wg == 1) {
                    sts_f(mxa + 1536 + w * 4, reduce8<false>(v, lane));
                    bar_arrive(4, 160);
                }
                mbar_wait(bars + 8 * BAR_PM);
                if (tid == 0) TL(9);
                float fo[4], fp[4];
                {
                    const int hd = 8 * (g >> 1) + 2 * t + (g & 1);
                    const float mo = lds_f(sb + OFF_PM + hd * 4), mp = lds_f(sb + OFF_PM + 128 + hd * 4);
                    const float mm = fmaxf(mo, mp), ao = ex2(mo - mm), ap = ex2(mp - mm);
#pragma unroll
                    for (int n = 0; n < 4; n++) {
                        fo[n] = __shfl_sync(~0u, ao, 4 * n + t);
                        fp[n] = __shfl_sync(~0u, ap, 4 * n + t);
                    }
                }
#pragma unroll
                for (int hp = 0; hp < 2; hp++) {
                    mbar_wait(bars + 8 * (BAR_PD + hp));
                    if (tid == 0) TL(hp ? 63 : 62);
                    const uint4 r0 = lds_u4(sb + OFF_PD + hp * 8192 + tid * 16), r1 = lds_u4(sb + OFF_PD + hp * 8192 + 4096 + tid * 16);
                    const uint32_t rw[8] = {r0.x, r0.y, r0.z, r0.w, r1.x, r1.y, r1.z, r1.w};
#pragma unroll
                    for (int n = 0; n < 4; n++) {
                        const int a = 4 * (n >> 1) + (n & 1);
                        float v[4];
#pragma unroll
                        for (int q = 0; q < 4; q++) {
                            const float own = o[2 * hp + (q >> 1)][a + 2 * (q & 1)];
                            const uint32_t wv = rw[2 * n + (q >> 1)];
                            v[q] = fmaf(own, fo[n], ((q & 1) ? bf_hi(wv) : bf_lo(wv)) * fp[n]);
                        }
                        st_x64(dst + (8 * (n >> 1) + (n & 1)) * 8 * 1024 + hp * 1024, make_uint2(set_tag<1>(pack_bf16(v[0], v[1]), tag), pack_bf16(v[2], v[3])));
                    }
                    __syncwarp();
                    if (lane == 0) red_add1(cnt + hp * 32);
                }
            }
        }
        TLM(22);
        if (tid == 0) TLG(60);
        if (warp == 0) {
            OutTile ot;
            ot.setup(sb, cta, 8, lane);
            ot.prefetch(sb);
            ot.finish(sb, p.s, 8, lane, tag + 1 TLPASS);
        }
    } else if (warp < 16) {
        if (REG_W > 96) asm volatile("setmaxnreg.inc.sync.aligned.u32 %0;" ::"n"(REG_W));
        const int ww = warp - 8, wt = tid - 256;
        const int lq = lane >> 3, li = lane & 7;
        const int b3 = ww >> 1, hp = ww & 1;
        const uint32_t epoch0 = ld_x32(&p.s->epoch[cta * 32]);
        const uint32_t* c3p = &p.s->c3[((b3 * 2 + (h >> 4)) * 8 + 2 * j + hp) * 32];
        const uint32_t c3v = ld_x32(c3p);
        const float b2v = ldg_bf(p.b2);
        if (t < 2) {
            const uint4 z = make_uint4(0, 0, 0, 0);
            st_x(&p.s->e1[cta * 128 + ww * 16 + 2 * g + t], z);
            st_x(&p.s->e4[cta * 128 + ww * 16 + 2 * g + t], z);
            uint4* d5 = &p.s->e5[((j * 18 + 2 * ww + (g >> 2)) * NH + h) * 8 + 2 * (g & 3) + t];
            st_x(d5, z);
            if (ww == 0) st_x(d5 + 16 * NH * 8, z);
        }
        bar_sync(6, NSTART);
        cluster_arrive();
        if (wt < FPH) {
            const uint32_t ra = sb + OFF_RAW + wt * 2;
            const float w1 = lds_bf(ra), bb = lds_bf(ra + 288), w2h = 0.5f * lds_bf(ra + 576);
            const float c1 = 0.7978845608028654f, c3 = c1 * 0.044715f;
            const uint32_t al[4] = {split_bf16(bb * fmaf(c3 * bb, bb, c1)), split_bf16(w1 * fmaf(3.f * c3 * bb, bb, c1)),
                                    split_bf16(3.f * c3 * w1 * w1 * bb), split_bf16(c3 * w1 * w1 * w1)};
            const uint32_t kk[2] = {split_bf16(w2h * bb), split_bf16(w2h * w1)};
#pragma unroll
            for (int q = 0; q < 4; q++)
                sts_u4(sb + OFF_MB + wt * 64 + q * 16,
                       make_uint4(__byte_perm(al[q], 0, 0x1010), __byte_perm(al[q], 0, 0x3232),
                                  q < 2 ? __byte_perm(kk[q & 1], 0, 0x1010) : 0u, q < 2 ? __byte_perm(kk[q & 1], 0, 0x3232) : 0u));
        }
        if (ww < 5) bar_arrive(5, 416);
        const uint32_t epoch = next_epoch(epoch0), tag = epoch & 1, tag2 = tag + 1;
        if (wt == 0) asm volatile("st.shared.u32 [%0], %1;" ::"r"(sb + OFF_EPOCH), "r"(epoch) : "memory");
        int it = 0;
        const uint32_t own = sb + OFF_STAGE + ww * 256 + (2 * g + t) * 16;
        const uint32_t arow = (8 * (lq >> 1) + li) * 128;
        const uint32_t aoff = arow + (((2 * (ww & 3) + (lq & 1)) ^ li) << 4);

        cluster_wait();
        mbar_wait(bars + 8 * (BAR_WQ + (ww >> 2)));
        if (wt == 0) TL(30);
        {
            uint4 a[9];
#pragma unroll
            for (int k = 0; k < 9; k++) a[k] = ldsm4t(sb + OFF_WQ + (ww >> 2) * 18432 + aoff + k * 2048);
            gemv_publish<9, false>(a, sb + OFF_X + ((li & 3) * DM + 144 * j) * 2 + lq * 16, &p.s->e1[cta * 128 + ww * 16 + 2 * g + t], own, t, tag2);
        }
        TLM(39);
        gather_sum(sb, &p.s->e1[((cta & ~3) + t) * 128 + ww * 16 + g], j, ww, lane, tag2, it, 31, [] {});
        TLM(43);
        bar_sync(1, 256);
        if (wt == 0) TL(2);

        {
            mbar_wait(bars + 8 * BAR_WK);
            mbar_wait(bars + 8 * (BAR_WK + 1));
            if (wt == 0) TL(1);
            float c0[4] = {}, c1[4] = {};
            const uint32_t abase = sb + OFF_WUV + (16 * ww + 8 * (lq & 1) + li) * 128;
            const uint32_t bbase = sb + OFF_QS + (g & 3) * 64 + t * 16;
#pragma unroll
            for (int k2 = 0; k2 < 4; k2++) {
                const uint4 bv = lds_u4(bbase + k2 * 256);
                const uint4 a0 = ldsm4(abase + (k2 >> 1) * 16384 + (((4 * (k2 & 1) + (lq >> 1)) ^ li) << 4));
                const uint4 a1 = ldsm4(abase + (k2 >> 1) * 16384 + (((4 * (k2 & 1) + 2 + (lq >> 1)) ^ li) << 4));
                mma16816(c0, a0.x, a0.y, a0.z, a0.w, bv.x, bv.y);
                mma16816(c1, a1.x, a1.y, a1.z, a1.w, bv.z, bv.w);
            }
            const float sc = 0.08838834764831845f * 1.4426950408889634f;
            const uint32_t stg = sb + OFF_STAGE + ww * 256;
            stsm2t(stg + li * 32 + (lq & 1) * 16, pack_bf16((c0[0] + c1[0]) * sc, (c0[1] + c1[1]) * sc),
                   pack_bf16((c0[2] + c1[2]) * sc, (c0[3] + c1[3]) * sc));
            __syncwarp();
            if (lane < 16) {
                uint4 v = lds_u4(stg + (lane & 7) * 16);
                v.x = set_tag<1>(v.x, tag);
                v.z = set_tag<1>(v.z, tag);
                st_x(&p.s->e2[(lane >> 1) * 2048 + (2 * j + (ww >> 2)) * 256 + (h ^ (2 * (lane & 8))) * 8 + ((2 * (ww & 3) + (lane & 1)) ^ (h & 7))], v);
            }
            TLM(44);
            bar_sync(1, 256);
            if (wt == 0) {
                red_add1(p.s->c2);
                mbar_arrive(bars + 8 * BAR_WKFREE);
            }
        }
        if (wt == 0) TL(3);

        OutTile ot;
        uint32_t e4w = cta * 128 + ww * 16 + 2 * g + t, e4r = ((cta & ~3) + t) * 128 + ww * 16 + g;
        asm volatile("" : "+r"(e4w), "+r"(e4r));
        mbar_wait(bars + 8 * (BAR_UV + (ww >> 2)));
        uint4 auv[8];
#pragma unroll
        for (int k = 0; k < 8; k++) auv[k] = ldsm4t(sb + OFF_WUV + (ww >> 2) * 16384 + aoff + k * 2048);
        mbar_wait(bars + 8 * BAR_LATE);
        if (wt == 0) TL(4);
        uint32_t e3o = (cta * 2 + hp) * 512 + (b3 * 16 + 2 * t) * 8 + g, sto = ((b3 * 2 + (h >> 4)) * 16 + (lane >> 1)) * 16 + (h & 15);
        uint32_t bma = sb + OFF_BM + frag_off(b3, 64 * hp + 32 * (t & 1) + 16 * (g >> 2) + 2 * (g & 3) + (t >> 1));
        asm volatile("" : "+r"(e3o), "+r"(sto), "+r"(bma));
        wait_count1(c3p, c3v, epoch * 32, it);
        const uint4* e3r = &p.s->e3[e3o];
        const uint2* stat_p = &p.s->stats[sto];
        TLM(6);
        {
            uint4 v[4];
            uint2 st;
            const int it0 = it;
            (void)it0;
#pragma unroll 1
            for (;;) {
                st = ld_x64(stat_p);
                v[0] = ld_x(e3r);
                v[1] = ld_x(e3r + 8);
                v[2] = ld_x(e3r + 64);
                v[3] = ld_x(e3r + 72);
                if (!__any_sync(~0u, ((st.y ^ tag) | tag_bad(v[0], tag) | tag_bad(v[1], tag) | tag_bad(v[2], tag) | tag_bad(v[3], tag)) & 1)) break;
                spin_check(it);
            }
            const float mm = __uint_as_float(ord_flip(__reduce_max_sync(~0u, (int)st.x)));
            const float wp = ex2(__uint_as_float(ord_flip(st.x)) - mm);
            const uint32_t pr = pack_bf16(wp, __shfl_down_sync(~0u, wp, 2));
            const uint32_t wa0 = __shfl_sync(~0u, pr, 4 * t), wa1 = __shfl_sync(~0u, pr, 4 * t + 16);
            float ls = wp * __uint_as_float(st.y);
#pragma unroll
            for (int o = 16; o > 1; o >>= 1) ls += __shfl_xor_sync(~0u, ls, o);
            const float inv = rcp_fast(ls);
            TLM(46);
            float lo[4], hi[4];
#pragma unroll
            for (int wd = 0; wd < 4; wd++) {
                const uint32_t r0 = (&v[0].x)[wd], r1 = (&v[1].x)[wd], r2 = (&v[2].x)[wd], r3 = (&v[3].x)[wd];
                float c[4] = {};
                mma16816(c, __byte_perm(r0, r1, 0x5410), __byte_perm(r0, r1, 0x7632), __byte_perm(r2, r3, 0x5410), __byte_perm(r2, r3, 0x7632), wa0, wa1);
                lo[wd] = c[0];
                hi[wd] = c[2];
            }
            const float l = (t & 2) ? ((t & 1) ? lo[3] : lo[2]) : ((t & 1) ? lo[1] : lo[0]);
            const float u = (t & 2) ? ((t & 1) ? hi[3] : hi[2]) : ((t & 1) ? hi[1] : hi[0]);
            const uint32_t pk = pack_bf16(l * inv, u * inv);
            sts_u16(bma, pk);
            sts_u16(bma + 4, pk >> 16);
        }
        TLM(7);
        if (wt == 0) TLG(61);

        {
            bar_sync(1, 256);
        if (wt == 0) TL(8);
            gemv_publish<8, true>(auv, sb + OFF_BM + (g & 3) * 64 + t * 16, &p.s->e4[e4w], own, t, tag2);
            TLM(40);
            gather_sum(sb, &p.s->e4[e4r], j, ww, lane, tag2, it, 56, [&] {
                ot.setup(sb, cta, ww, lane);
                ot.prefetch(sb);
            });
        }
        TLM(42);

        ot.finish(sb, p.s, ww, lane, tag2 TLPASS);
        TLM(10);

        if (cta < 72 && ww == 1) {
            const uint4* src = &p.s->e5[(cta * NH + lq) * 8 + li];
            const int bb = 2 * (lane & 1) + (lq & 1);
            const float bias = (1.f - lds_f(sb + OFF_GATE + bb * 4)) * b2v;
            uint4 v[8];
#pragma unroll 1
            for (;;) {
#pragma unroll
                for (int i = 0; i < 8; i++) v[i] = ld_x(src + i * 32);
                uint32_t bad = 0;
#pragma unroll
                for (int i = 0; i < 8; i++) bad |= tag_bad(v[i], tag2);
                if (!__any_sync(~0u, bad & 3)) break;
                spin_check(it);
            }
            if (lane == 0) { TL(47); TLV(48, it - it0 + 1); TLV(58, ((uint32_t)clock() - c0_) / (uint32_t)(it - it0 + 1)); }
            float x[4];
#pragma unroll
            for (int e = 0; e < 4; e++)
                x[e] = ((__uint_as_float((&v[0].x)[e]) + __uint_as_float((&v[1].x)[e])) + (__uint_as_float((&v[2].x)[e]) + __uint_as_float((&v[3].x)[e]))) +
                       ((__uint_as_float((&v[4].x)[e]) + __uint_as_float((&v[5].x)[e])) + (__uint_as_float((&v[6].x)[e]) + __uint_as_float((&v[7].x)[e])));
            const bool hi = lane & 16, od = lane & 8;
            const float a0 = (hi ? x[2] : x[0]) + __shfl_xor_sync(~0u, hi ? x[0] : x[2], 16);
            const float a1 = (hi ? x[3] : x[1]) + __shfl_xor_sync(~0u, hi ? x[1] : x[3], 16);
            const float r = (od ? a1 : a0) + __shfl_xor_sync(~0u, od ? a0 : a1, 8);
            const int line = cta % 18;
            p.out[bb * DM + (cta / 18) * MQ + 16 * (line >> 1) + 4 * (line & 1) + (li >> 1) + 8 * (lq >> 1)] = __float2bfloat16(r + bias);
            if (lane == 0) TL(11);
        }
        if (wt == 32) st_x32(&p.s->epoch[cta * 32], epoch);
    } else {
        if (warp == 16) {
            if (lane == 0) TL(33);
            uint64_t pol;
            asm volatile("createpolicy.fractional.L2::evict_first.b64 %0, 1.0;" : "=l"(pol));
            if (lane == 0) {
#pragma unroll
                for (int n = 0; n < 2; n++) mbar_init(bars + 8 * (BAR_WQ + n), 1);
                fence_async_smem();
                TL(34);
#pragma unroll
                for (int n = 0; n < 2; n++) {
                    mbar_expect_tx(bars + 8 * (BAR_WQ + n), 18432);
                    tma3(sb + OFF_WQ + n * 18432, &map_q, h * 128 + 64 * n, 144 * j, 0, bars + 8 * (BAR_WQ + n), pol);
                }
                TL(35);
            }
            __syncwarp();
        }
        asm volatile("setmaxnreg.dec.sync.aligned.u32 %0;" ::"n"(REG_P));
        if (warp == 16) {
            const uint64_t t_begin = gtime();
            uint64_t pol;
            asm volatile("createpolicy.fractional.L2::evict_first.b64 %0, 1.0;" : "=l"(pol));
            if (lane == 0) {
#pragma unroll
                for (int i = 2; i < NBAR; i++) mbar_init(bars + 8 * i, i == BAR_C0FREE || i == BAR_PF ? 8 : i == BAR_WKFREE ? 9 : 1);
                mbar_expect_tx(bars + 8 * BAR_PM, 256);
                mbar_expect_tx(bars + 8 * BAR_PL, 128);
                mbar_expect_tx(bars + 8 * BAR_PD, 8192);
                mbar_expect_tx(bars + 8 * (BAR_PD + 1), 8192);
                asm volatile("fence.mbarrier_init.release.cluster;" ::: "memory");
                fence_async_smem();
            }
            __syncwarp();
            bar_arrive(6, NSTART);
            cluster_arrive();
            const int n = lane + BAR_WK;
            const CUtensorMap* mp;
            int c0, c1, c2, wait2 = -1;
            uint32_t dst, bytes = 16384;
            if (n < BAR_C) {
                mp = &map_uk; c0 = h * 128 + 64 * lane; c1 = 0; c2 = 2 * j; dst = OFF_WUV + lane * 16384;
            } else if (n < BAR_UV) {
                mp = &map_c; c0 = 0; c1 = cta * 128 + 64 * ((n - BAR_C) >> 2); c2 = 2 * (n & 3); dst = OFF_C + (n - BAR_C) * 16384;
                if (n == BAR_C + 4) wait2 = BAR_WKFREE;
            } else if (n < BAR_WO) {
                mp = &map_uv; c0 = h * 128 + 64 * (n - BAR_UV); c1 = 32 * (j & 1); c2 = 4 * (j >> 1); dst = OFF_WUV + (n - BAR_UV) * 16384;
            } else {
                mp = &map_o; c0 = MQ * j; c1 = h * 128 + 32 * (n - BAR_WO); c2 = 0; dst = OFF_C + (n - BAR_WO) * (32 * WOP); bytes = 32 * WOP;
                if (n == BAR_WO) wait2 = BAR_C0FREE;
            }
            int before = 36864 + 16384 * (n - BAR_WK);
            if (n >= BAR_WO) before = 36864 + 12 * 16384 + 9216 * (n - BAR_WO);
            int gap = bytes;
            if (STAGGER && n >= BAR_C && n < BAR_UV) {
                const int k = n - BAR_C;
                gap = !(cta & 1) ? SPAN1 / 8 : k < 4 ? SPAN1 / 4 : (131072 - SPAN1) / 4;
                before = 36864 + 32768 + (!(cta & 1) || k < 4 ? k * gap : SPAN1 + (k - 4) * gap);
            }
            if (PHASE) before += (((cta >> 1) * 37 + (cta & 1) * 32) & 63) * (gap / 64) * (n >= BAR_C && n < BAR_UV ? 8 - TAPER * (n - BAR_C) : 8) / 8;
            if (n >= BAR_UV) before = 36864 + 10 * 16384 + (int)((before - (36864 + 10 * 16384)) * TAILSLOW) + TAILGAP;
            const uint64_t due = t_begin + (uint64_t)(n < BAR_C && n - BAR_WK < WKEARLY ? 0 : max(0, (int)(before * (1.f / RATE)) - LEAD));
            const uint32_t fb = bars + 8 * (n > BAR_WO ? BAR_WO : n);
            const uint32_t expect = n == BAR_WO ? 4 * 32 * WOP : n > BAR_WO ? 0 : bytes;
            const int wait1 = n - WMAX;
            if (lane == 1) {
                asm volatile("prefetch.tensormap [%0];" ::"l"(&map_c) : "memory");
                asm volatile("prefetch.tensormap [%0];" ::"l"(&map_uv) : "memory");
                asm volatile("prefetch.tensormap [%0];" ::"l"(&map_o) : "memory");
            }
#pragma unroll 1
            for (int k = 0; k < NPIECE - BAR_WK; k++) {
                if (lane == k) {
                    int it = 0;
#pragma unroll 1
                    while (gtime() < due) { if (PSLEEP) __nanosleep(PSLEEP); spin_check(it); }
                    if (wait1 >= 0) mbar_wait(bars + 8 * wait1);
                    if (wait2 >= 0) mbar_wait(bars + 8 * wait2);
                    if (expect) mbar_expect_tx(fb, expect);
                    tma3(sb + dst, mp, c0, c1, c2, fb, pol);
                }
                __syncwarp();
            }
        }
        else if (warp == 17) {
            uint32_t c2v = ld_x32(p.s->c2);
            bar_sync(6, NSTART);
            cluster_arrive();
            cluster_wait();
            if (lane == 0) {
                mbar_wait(bars + 8 * BAR_WKFREE);
                const uint32_t want = lds_u32(sb + OFF_EPOCH) * NCTA;
                int it = 0;
#pragma unroll 1
                while (c2v != want) {
                    c2v = ld_x32(p.s->c2);
                    spin_check(it);
                }
                TL(41);
                mbar_expect_tx(bars + 8 * BAR_Q, 32768);
                bulk_load(sb + OFF_Q, &p.s->e2[(rank * 4 + (cta >> 5)) * 2048], 32768, bars + 8 * BAR_Q);
            }
            __syncwarp();
            mbar_wait(bars + 8 * BAR_LATE);
            const uint32_t a = sb + OFF_MX + lane * 16;
            const float m0 = max4(lds_f4(a)), m1 = fmaxf(m0, max4(lds_f4(a + 512)));
            st_peer1(map_peer(sb + OFF_PM + 128 + (lane ^ 16) * 4, rank ^ 1), m1, map_peer(bars + 8 * BAR_PM, rank ^ 1));
            st_peer1(map_peer(sb + OFF_PM + lane * 4, rank), m1, map_peer(bars + 8 * BAR_PM, rank));
            bar_sync(4, 160);
            const float l = fmaf(sum4(lds_f4(a + 1024)), ex2(m0 - m1), sum4(lds_f4(a + 1536)));
            st_peer1(map_peer(sb + OFF_PL + (lane ^ 16) * 4, rank ^ 1), l, map_peer(bars + 8 * BAR_PL, rank ^ 1));
            mbar_wait(bars + 8 * BAR_PM);
            mbar_wait(bars + 8 * BAR_PL);
            const float mp = lds_f(sb + OFF_PM + 128 + lane * 4), mm = fmaxf(m1, mp);
            const float lp = fmaf(l, ex2(m1 - mm), lds_f(sb + OFF_PL + lane * 4) * ex2(mp - mm));
            if (lane < 16)
                st_x64(&p.s->stats[(((cta >> 5) * 2 + rank) * 16 + ((cta >> 1) & 15)) * 16 + lane],
                       make_uint2(ord_flip(__float_as_uint(mm)), set_tag<1>(__float_as_uint(lp), lds_u32(sb + OFF_EPOCH) & 1)));
        }
    }
}

typedef CUresult (*EncodeFn)(CUtensorMap*, CUtensorMapDataType, cuuint32_t, void*, const cuuint64_t*, const cuuint64_t*,
                             const cuuint32_t*, const cuuint32_t*, CUtensorMapInterleave, CUtensorMapSwizzle,
                             CUtensorMapL2promotion, CUtensorMapFloatOOBfill);

void make_map3(EncodeFn enc, CUtensorMap* m, const void* base, uint64_t d0, uint64_t d1, uint64_t d2, uint64_t s1, uint64_t s2,
               uint32_t b0, uint32_t b1, uint32_t b2, CUtensorMapSwizzle sw = CU_TENSOR_MAP_SWIZZLE_128B) {
    cuuint64_t dims[3] = {d0, d1, d2}, strides[2] = {s1, s2};
    cuuint32_t box[3] = {b0, b1, b2}, es[3] = {1, 1, 1};
    enc(m, CU_TENSOR_MAP_DATA_TYPE_BFLOAT16, 3, const_cast<void*>(base), dims, strides, box, es, CU_TENSOR_MAP_INTERLEAVE_NONE,
        sw, CU_TENSOR_MAP_L2_PROMOTION_L2_128B, CU_TENSOR_MAP_FLOAT_OOB_FILL_NONE);
}

}

extern "C" void kernel_launch(void* const* d_in, const int* in_sizes, int n_in, void* d_out, int out_size) {
    (void)in_sizes; (void)n_in; (void)out_size;
    static EncodeFn enc = nullptr;
    static void* scratch = nullptr;
    if (!enc) {
        void* fn = nullptr;
        cudaDriverEntryPointQueryResult qr;
        cudaGetDriverEntryPoint("cuTensorMapEncodeTiled", &fn, cudaEnableDefault, &qr);
        enc = reinterpret_cast<EncodeFn>(fn);
        cudaGetSymbolAddress(&scratch, g_scratch);
        cudaFuncSetAttribute(fused_decode_kernel, cudaFuncAttributeMaxDynamicSharedMemorySize, SMEM_BYTES);
    }
    CUtensorMap mq, mc, muk, muv, mo;
    make_map3(enc, &mc, d_in[1], 64, (uint64_t)NB * SK, 8, DC * 2, 128, 64, 64, 2);
    make_map3(enc, &mq, d_in[2], NH * DH, DM, 1, NH * DH * 2, (uint64_t)DM * NH * DH * 2, 64, 144, 1);
    make_map3(enc, &muk, d_in[3], NH * DH, 64, 8, NH * DH * 2, (uint64_t)64 * NH * DH * 2, 64, 64, 2);
    make_map3(enc, &muv, d_in[4], NH * DH, 64, 8, NH * DH * 2, (uint64_t)64 * NH * DH * 2, 64, 32, 4);
    make_map3(enc, &mo, d_in[5], DM, NH * DH, 1, DM * 2, (uint64_t)DM * NH * DH * 2, WOP / 2, 32, 1, CU_TENSOR_MAP_SWIZZLE_NONE);
    Params p;
    p.x = static_cast<const __nv_bfloat16*>(d_in[0]);
    p.w1 = static_cast<const __nv_bfloat16*>(d_in[7]);
    p.b1 = static_cast<const __nv_bfloat16*>(d_in[8]);
    p.w2 = static_cast<const __nv_bfloat16*>(d_in[9]);
    p.b2 = static_cast<const __nv_bfloat16*>(d_in[10]);
    p.gate_w = static_cast<const __nv_bfloat16*>(d_in[11]);
    p.out = static_cast<__nv_bfloat16*>(d_out);
    p.s = static_cast<Scratch*>(scratch);
    fused_decode_kernel<<<NCTA, NTHREADS, SMEM_BYTES>>>(p, mq, muk, mc, muv, mo);
}
```

```cpp
#include <cuda_runtime.h>
#include <cuda_bf16.h>
#include <cuda.h>
#include <stdint.h>

namespace {

constexpr int NB = 4, NH = 32, SK = 4096, DH = 128, DM = 576, DC = 512, NF = 4608;
constexpr int NCTA = 128;
constexpr int NTHREADS = 640;
constexpr int FPH = NF / NH;
constexpr int MQ = DM / 4;
constexpr int WOP = 304;

#define SWAP 0
#define ORDER 0xFEDCBA9876543210ull
#define NTMAX 9
#define RELEASE 6
#define RATE 26.5f
#define LEAD 600
#define WKT0 0
#define WKT1 0
#define TAILGAP 0
#define FACT_AT 1
#define EARLYDESC 1
#define WQSWAP 0
#define WQSLEEP 0
#define PHASE 8
#define WMAX 6
#define REG_A 120
#define REG_W 96
#define REG_P 40
constexpr int SPIN_LIMIT = 1 << 20;

constexpr int OFF_C = 0;
constexpr int OFF_PD = 40960;
constexpr int OFF_WQ = 57344;
constexpr int OFF_Q = 131072;
constexpr int OFF_WUV = OFF_Q + 32768;
constexpr int OFF_P = OFF_WUV + 32768;
constexpr int OFF_MB = OFF_P;
constexpr int OFF_Y = OFF_P + 9216;
constexpr int OFF_MA = OFF_Y;
constexpr int OFF_STAGE = OFF_MA + 9216;
constexpr int OFF_PQ = OFF_STAGE + 2048;
constexpr int OFF_QS = OFF_PQ + 2048;
constexpr int OFF_BM = OFF_QS + 1024;
constexpr int OFF_X = OFF_BM + 1024;
constexpr int OFF_GW = OFF_X + 4608;
constexpr int OFF_RAW = OFF_GW + 1152;
constexpr int OFF_STAT = OFF_RAW + 864;
constexpr int OFF_GATE = OFF_STAT + 128;
constexpr int OFF_EPOCH = OFF_GATE + 16;
constexpr int OFF_PM = OFF_EPOCH + 48;
constexpr int OFF_PL = OFF_PM + 256;
constexpr int OFF_MX = OFF_PL + 128;
constexpr int OFF_LSUM = OFF_MX + 1024;
constexpr int OFF_BAR = OFF_LSUM + 1024;
constexpr int SMEM_BYTES = OFF_BAR + 384, NSTART = 576;
static_assert(SMEM_BYTES <= 232448, "shared memory budget");

constexpr int NPIECE = 18;
constexpr int BAR_WQ = 0, BAR_WK = 2, BAR_C = 4, BAR_UV = 12, BAR_WO = 14;
constexpr int BAR_C0FREE = 18;
constexpr int BAR_WKFREE = 19;
constexpr int BAR_LATE = 20;
constexpr int BAR_Q = 21;
constexpr int BAR_PM = 22;
constexpr int BAR_PD = 23;
constexpr int BAR_PF = 25;
constexpr int BAR_PL = 26;
constexpr int BAR_WQ2 = 27;
constexpr int BAR_WQFREE = 29;
constexpr int BAR_PQ = 30;
constexpr int BAR_MA = 31;
constexpr int NBAR = 32;
constexpr float LAZY_LIMIT = 1024.f;

struct Scratch {
    uint4 e3[NCTA * 64 * 16];
    uint4 e5[72 * NH * 8];
    uint4 e4[NCTA * 128];
    uint4 e2[2 * NB * 2048];
    uint2 stats[NCTA * 16];
    uint32_t c3[NB * 16 * 32];
    uint32_t c2[32];
    uint32_t epoch[NCTA * 32];
};
__device__ __align__(1024) Scratch g_scratch;
#define TLARG
#define TLPASS
#define TLM(i) do {} while (0)
#define TLG(i) do {} while (0)
#define TLV(i, v) do {} while (0)
#define TL(i) do {} while (0)

__device__ __forceinline__ uint32_t smem_u32(const void* p) { return (uint32_t)__cvta_generic_to_shared(p); }
__device__ __forceinline__ void mbar_init(uint32_t bar, int cnt) {
    asm volatile("mbarrier.init.shared::cta.b64 [%0], %1;" ::"r"(bar), "r"(cnt) : "memory");
}
__device__ __forceinline__ void mbar_expect_tx(uint32_t bar, uint32_t bytes) {
    asm volatile("mbarrier.arrive.expect_tx.shared::cta.b64 _, [%0], %1;" ::"r"(bar), "r"(bytes) : "memory");
}
__device__ __forceinline__ void mbar_arrive(uint32_t bar) {
    asm volatile("mbarrier.arrive.shared::cta.b64 _, [%0];" ::"r"(bar) : "memory");
}
__device__ __forceinline__ void mbar_wait(uint32_t bar, uint32_t parity = 0) {
    asm volatile(
        "{\n.reg .pred p;\n.reg .u32 c;\nmov.u32 c, 0;\n"
        "WAIT_LOOP:\nmbarrier.try_wait.parity.shared::cta.b64 p, [%0], %2;\n@p bra WAIT_DONE;\n"
        "add.u32 c, c, 1;\nsetp.lt.u32 p, c, %1;\n@p bra WAIT_LOOP;\ntrap;\nWAIT_DONE:\n}"
        ::"r"(bar), "n"(SPIN_LIMIT), "r"(parity) : "memory");
}
__device__ __forceinline__ bool bar_or(int id, int n, bool v) {
    uint32_t r;
    asm volatile("{\n.reg .pred p, q;\nsetp.ne.u32 q, %3, 0;\nbar.red.or.pred p, %1, %2, q;\nselp.u32 %0, 1, 0, p;\n}"
                 : "=r"(r) : "r"(id), "r"(n), "r"((uint32_t)v) : "memory");
    return __any_sync(~0u, r);
}
__device__ __forceinline__ void bar_sync(int id, int n) { asm volatile("bar.sync %0, %1;" ::"r"(id), "r"(n) : "memory"); }
__device__ __forceinline__ void fence_async_smem() { asm volatile("fence.proxy.async.shared::cta;" ::: "memory"); }
__device__ __forceinline__ void tma3(uint32_t dst, const CUtensorMap* m, int c0, int c1, int c2, uint32_t bar, uint64_t pol) {
    asm volatile(
        "cp.async.bulk.tensor.3d.shared::cluster.global.mbarrier::complete_tx::bytes.L2::cache_hint [%0], [%1, {%2, %3, %4}], [%5], %6;"
        ::"r"(dst), "l"(m), "r"(c0), "r"(c1), "r"(c2), "r"(bar), "l"(pol) : "memory");
}
__device__ __forceinline__ void bulk_load(uint32_t dst, const void* src, uint32_t bytes, uint32_t bar) {
    asm volatile("cp.async.bulk.shared::cluster.global.mbarrier::complete_tx::bytes [%0], [%1], %2, [%3];"
                 ::"r"(dst), "l"(src), "r"(bytes), "r"(bar) : "memory");
}
__device__ __forceinline__ uint32_t lds_u32(uint32_t a) { uint32_t v; asm volatile("ld.shared.u32 %0, [%1];" : "=r"(v) : "r"(a) : "memory"); return v; }
__device__ __forceinline__ float lds_bf(uint32_t a) {
    unsigned short v;
    asm volatile("ld.shared.u16 %0, [%1];" : "=h"(v) : "r"(a) : "memory");
    return __uint_as_float((uint32_t)v << 16);
}
__device__ __forceinline__ uint4 ld_x(const uint4* p) {
    uint4 v;
    asm volatile("{\n.reg .b64 a, b;\nld.relaxed.gpu.global.v2.b64 {a, b}, [%4];\nmov.b64 {%0,%1}, a;\nmov.b64 {%2,%3}, b;\n}"
                 : "=r"(v.x), "=r"(v.y), "=r"(v.z), "=r"(v.w) : "l"(p) : "memory");
    return v;
}
__device__ __forceinline__ void st_x(uint4* p, uint4 v) {
    asm volatile("{\n.reg .b64 a, b;\nmov.b64 a, {%1,%2};\nmov.b64 b, {%3,%4};\nst.relaxed.gpu.global.v2.b64 [%0], {a, b};\n}"
                 ::"l"(p), "r"(v.x), "r"(v.y), "r"(v.z), "r"(v.w) : "memory");
}
__device__ __forceinline__ uint2 ld_x64(const uint2* p) {
    uint2 v;
    asm volatile("{\n.reg .b64 a;\nld.relaxed.gpu.global.b64 a, [%2];\nmov.b64 {%0,%1}, a;\n}" : "=r"(v.x), "=r"(v.y) : "l"(p) : "memory");
    return v;
}
__device__ __forceinline__ void st_x64(uint2* p, uint2 v) {
    asm volatile("{\n.reg .b64 a;\nmov.b64 a, {%1,%2};\nst.relaxed.gpu.global.b64 [%0], a;\n}" ::"l"(p), "r"(v.x), "r"(v.y) : "memory");
}
__device__ __forceinline__ uint32_t ld_x32(const uint32_t* p) {
    uint32_t v;
    asm volatile("ld.relaxed.gpu.global.u32 %0, [%1];" : "=r"(v) : "l"(p) : "memory");
    return v;
}
__device__ __forceinline__ void st_x32(uint32_t* p, uint32_t v) { asm volatile("st.relaxed.gpu.global.u32 [%0], %1;" ::"l"(p), "r"(v) : "memory"); }
template <uint32_t MASK>
__device__ __forceinline__ uint32_t set_tag(uint32_t w, uint32_t tag) {
    uint32_t r;
    asm("lop3.b32 %0, %1, %2, %3, 0xEA;" : "=r"(r) : "r"(w), "n"(~MASK), "r"(tag));
    return r;
}
__device__ __forceinline__ uint32_t tag_bad(uint4 v, uint32_t tag) {
    uint32_t r;
    asm("lop3.b32 %0, %1, %2, %3, 0x7E;" : "=r"(r) : "r"(v.x), "r"(v.z), "r"(tag));
    return r;
}
__device__ __forceinline__ uint4 tag4(float a, float b, float c, float d, uint32_t tag) {
    return make_uint4(set_tag<3>(__float_as_uint(a), tag), __float_as_uint(b), set_tag<3>(__float_as_uint(c), tag), __float_as_uint(d));
}
__device__ __forceinline__ void red_add1(uint32_t* p) { asm volatile("red.relaxed.gpu.global.add.u32 [%0], 1;" ::"l"(p) : "memory"); }
__device__ __forceinline__ void spin_check(int& it) {
    if (++it > SPIN_LIMIT) asm volatile("trap;");
}
__device__ __forceinline__ float lds_f(uint32_t a) { float v; asm volatile("ld.shared.f32 %0, [%1];" : "=f"(v) : "r"(a) : "memory"); return v; }
__device__ __forceinline__ float4 lds_f4(uint32_t a) {
    float4 v;
    asm volatile("ld.shared.v4.f32 {%0,%1,%2,%3}, [%4];" : "=f"(v.x), "=f"(v.y), "=f"(v.z), "=f"(v.w) : "r"(a) : "memory");
    return v;
}
__device__ __forceinline__ uint4 lds_u4(uint32_t a) {
    uint4 v;
    asm volatile("ld.shared.v4.u32 {%0,%1,%2,%3}, [%4];" : "=r"(v.x), "=r"(v.y), "=r"(v.z), "=r"(v.w) : "r"(a) : "memory");
    return v;
}
__device__ __forceinline__ void sts_f(uint32_t a, float v) { asm volatile("st.shared.f32 [%0], %1;" ::"r"(a), "f"(v) : "memory"); }
__device__ __forceinline__ void sts_u16(uint32_t a, uint32_t v) { asm volatile("st.shared.u16 [%0], %1;" ::"r"(a), "h"((unsigned short)v) : "memory"); }
__device__ __forceinline__ void sts_u2(uint32_t a, uint32_t x, uint32_t y) { asm volatile("st.shared.v2.u32 [%0], {%1,%2};" ::"r"(a), "r"(x), "r"(y) : "memory"); }
__device__ __forceinline__ void sts_u4(uint32_t a, uint4 v) {
    asm volatile("st.shared.v4.u32 [%0], {%1,%2,%3,%4};" ::"r"(a), "r"(v.x), "r"(v.y), "r"(v.z), "r"(v.w) : "memory");
}
__device__ __forceinline__ void sts_f4(uint32_t a, float x, float y, float z, float w) {
    asm volatile("st.shared.v4.f32 [%0], {%1,%2,%3,%4};" ::"r"(a), "f"(x), "f"(y), "f"(z), "f"(w) : "memory");
}
__device__ __forceinline__ float2 lds_f2(uint32_t a) {
    float2 v;
    asm volatile("ld.shared.v2.f32 {%0,%1}, [%2];" : "=f"(v.x), "=f"(v.y) : "r"(a) : "memory");
    return v;
}
__device__ __forceinline__ void cp_async16(uint32_t dst, const void* src) {
    asm volatile("cp.async.cg.shared.global [%0], [%1], 16;" ::"r"(dst), "l"(src) : "memory");
}
__device__ __forceinline__ uint64_t gtime() { uint64_t t; asm volatile("mov.u64 %0, %%globaltimer;" : "=l"(t)); return t; }
__device__ __forceinline__ uint32_t map_peer(uint32_t addr, int rank) {
    uint32_t r;
    asm("mapa.shared::cluster.u32 %0, %1, %2;" : "=r"(r) : "r"(addr), "r"(rank));
    return r;
}
__device__ __forceinline__ void st_peer4(uint32_t addr, uint32_t a, uint32_t b, uint32_t c, uint32_t d, uint32_t bar) {
    asm volatile("st.async.weak.shared::cluster.mbarrier::complete_tx::bytes.v4.b32 [%0], {%1,%2,%3,%4}, [%5];"
                 ::"r"(addr), "r"(a), "r"(b), "r"(c), "r"(d), "r"(bar) : "memory");
}
__device__ __forceinline__ void st_peer1(uint32_t addr, float a, uint32_t bar) {
    asm volatile("st.async.weak.shared::cluster.mbarrier::complete_tx::bytes.f32 [%0], %1, [%2];" ::"r"(addr), "f"(a), "r"(bar) : "memory");
}
__device__ __forceinline__ void cluster_arrive() { asm volatile("barrier.cluster.arrive.relaxed.aligned;" ::: "memory"); }
__device__ __forceinline__ void cluster_wait() { asm volatile("barrier.cluster.wait.acquire.aligned;" ::: "memory"); }
__device__ __forceinline__ void bar_arrive(int id, int n) { asm volatile("bar.arrive %0, %1;" ::"r"(id), "r"(n) : "memory"); }
__device__ __forceinline__ float rcp_fast(float x) { float r; asm("rcp.approx.ftz.f32 %0, %1;" : "=f"(r) : "f"(x)); return r; }
__device__ __forceinline__ float rsq_fast(float x) { float r; asm("rsqrt.approx.ftz.f32 %0, %1;" : "=f"(r) : "f"(x)); return r; }
__device__ __forceinline__ float ldg_bf(const __nv_bfloat16* p) {
    unsigned short v;
    asm volatile("ld.global.nc.u16 %0, [%1];" : "=h"(v) : "l"(p));
    return __uint_as_float((uint32_t)v << 16);
}
__device__ __forceinline__ float max4(float4 v) { return fmaxf(fmaxf(v.x, v.y), fmaxf(v.z, v.w)); }
__device__ __forceinline__ float sum4(float4 v) { return (v.x + v.y) + (v.z + v.w); }
__device__ __forceinline__ uint32_t pack_bf16(float lo, float hi) {
    uint32_t r;
    asm("cvt.rn.bf16x2.f32 %0, %1, %2;" : "=r"(r) : "f"(hi), "f"(lo));
    return r;
}
__device__ __forceinline__ uint32_t split_bf16(float v) { return pack_bf16(v, v - __uint_as_float(pack_bf16(v, v) << 16)); }
__device__ __forceinline__ float bf_lo(uint32_t w) { return __uint_as_float(w << 16); }
__device__ __forceinline__ float bf_hi(uint32_t w) { return __uint_as_float(w & 0xFFFF0000u); }
__device__ __forceinline__ float ex2(float x) { float r; asm("ex2.approx.ftz.f32 %0, %1;" : "=f"(r) : "f"(x)); return r; }
__device__ __forceinline__ float tanh_fast(float x) { float r; asm("tanh.approx.f32 %0, %1;" : "=f"(r) : "f"(x)); return r; }
__device__ __forceinline__ void mma16816(float (&c)[4], uint32_t a0, uint32_t a1, uint32_t a2, uint32_t a3, uint32_t b0, uint32_t b1) {
    asm volatile("mma.sync.aligned.m16n8k16.row.col.f32.bf16.bf16.f32 {%0,%1,%2,%3}, {%4,%5,%6,%7}, {%8,%9}, {%0,%1,%2,%3};"
                 : "+f"(c[0]), "+f"(c[1]), "+f"(c[2]), "+f"(c[3]) : "r"(a0), "r"(a1), "r"(a2), "r"(a3), "r"(b0), "r"(b1));
}
__device__ __forceinline__ uint4 ldsm4(uint32_t a) {
    uint4 v;
    asm volatile("ldmatrix.sync.aligned.m8n8.x4.shared.b16 {%0,%1,%2,%3}, [%4];" : "=r"(v.x), "=r"(v.y), "=r"(v.z), "=r"(v.w) : "r"(a) : "memory");
    return v;
}
__device__ __forceinline__ uint4 ldsm4t(uint32_t a) {
    uint4 v;
    asm volatile("ldmatrix.sync.aligned.m8n8.x4.trans.shared.b16 {%0,%1,%2,%3}, [%4];" : "=r"(v.x), "=r"(v.y), "=r"(v.z), "=r"(v.w) : "r"(a) : "memory");
    return v;
}
__device__ __forceinline__ void stsm4t(uint32_t a, uint32_t r0, uint32_t r1, uint32_t r2, uint32_t r3) {
    asm volatile("stmatrix.sync.aligned.m8n8.x4.trans.shared.b16 [%0], {%1,%2,%3,%4};" ::"r"(a), "r"(r0), "r"(r1), "r"(r2), "r"(r3) : "memory");
}
__device__ __forceinline__ void stsm2t(uint32_t a, uint32_t r0, uint32_t r1) {
    asm volatile("stmatrix.sync.aligned.m8n8.x2.trans.shared.b16 [%0], {%1,%2};" ::"r"(a), "r"(r0), "r"(r1) : "memory");
}
__device__ __forceinline__ uint32_t make_desc(uint32_t addr) { return (addr >> 4) | (1u << 16); }
__device__ __forceinline__ void wg_fence() { asm volatile("wgmma.fence.sync.aligned;" ::: "memory"); }
__device__ __forceinline__ void wg_commit() { asm volatile("wgmma.commit_group.sync.aligned;" ::: "memory"); }
template <int N>
__device__ __forceinline__ void wg_wait() { asm volatile("wgmma.wait_group.sync.aligned %0;" ::"n"(N) : "memory"); }
template <int TA>
__device__ __forceinline__ void wgmma32(float (&d)[16], uint32_t da, uint32_t db) {
    asm volatile(
        "{\n.reg .b64 a, b;\nmov.b64 a, {%16, 0x40000040};\nmov.b64 b, {%17, 0x40000040};\n"
        "wgmma.mma_async.sync.aligned.m64n32k16.f32.bf16.bf16 "
        "{%0,%1,%2,%3,%4,%5,%6,%7,%8,%9,%10,%11,%12,%13,%14,%15}, a, b, 1, 1, 1, %18, 0;\n}\n"
        : "+f"(d[0]), "+f"(d[1]), "+f"(d[2]), "+f"(d[3]), "+f"(d[4]), "+f"(d[5]), "+f"(d[6]), "+f"(d[7]),
          "+f"(d[8]), "+f"(d[9]), "+f"(d[10]), "+f"(d[11]), "+f"(d[12]), "+f"(d[13]), "+f"(d[14]), "+f"(d[15])
        : "r"(da), "r"(db), "n"(TA));
}
__device__ __forceinline__ void reg_fence(float (&d)[16]) {
#pragma unroll
    for (int i = 0; i < 16; i++) asm volatile("" : "+f"(d[i])::"memory");
}
template <bool MAX>
__device__ __forceinline__ float reduce8(const float (&v)[8], int lane) {
    float a[4], b[2];
    const bool h4 = lane & 16, h2 = lane & 8, h1 = lane & 4;
#pragma unroll
    for (int i = 0; i < 4; i++) {
        float keep = h4 ? v[i + 4] : v[i], send = h4 ? v[i] : v[i + 4];
        float r = __shfl_xor_sync(~0u, send, 16);
        a[i] = MAX ? fmaxf(keep, r) : keep + r;
    }
#pragma unroll
    for (int i = 0; i < 2; i++) {
        float keep = h2 ? a[i + 2] : a[i], send = h2 ? a[i] : a[i + 2];
        float r = __shfl_xor_sync(~0u, send, 8);
        b[i] = MAX ? fmaxf(keep, r) : keep + r;
    }
    float keep = h1 ? b[1] : b[0], send = h1 ? b[0] : b[1];
    float r = __shfl_xor_sync(~0u, send, 4);
    return MAX ? fmaxf(keep, r) : keep + r;
}

struct Params {
    const __nv_bfloat16 *x, *w1, *b1, *w2, *b2, *gate_w;
    __nv_bfloat16* out;
    Scratch* s;
};

__device__ __forceinline__ void score_piece(float (&sc)[16], uint32_t sb, int s, int q) {
    const uint32_t da = make_desc(sb + OFF_C + s * 65536 + q * 16384), db = make_desc(sb + OFF_Q + q * 8192);
    wg_fence();
#pragma unroll
    for (int k = 0; k < 8; k++)
        wgmma32<0>(sc, da + (((k >> 2) * 8192 + (k & 3) * 32) >> 4), db + (((k >> 2) * 4096 + (k & 3) * 32) >> 4));
    wg_commit();
}

__device__ __forceinline__ void store_p(const float (&sc)[16], const float (&mr)[8], float (&v)[8], uint32_t pa) {
    uint32_t pk[8];
#pragma unroll
    for (int jj = 0; jj < 4; jj++) {
        const float p0 = ex2(sc[4 * jj] - mr[2 * jj]), p1 = ex2(sc[4 * jj + 1] - mr[2 * jj + 1]);
        const float p2 = ex2(sc[4 * jj + 2] - mr[2 * jj]), p3 = ex2(sc[4 * jj + 3] - mr[2 * jj + 1]);
        pk[2 * jj] = pack_bf16(p0, p1);
        pk[2 * jj + 1] = pack_bf16(p2, p3);
        v[2 * jj] = p0 + p2;
        v[2 * jj + 1] = p1 + p3;
    }
    stsm4t(pa, pk[0], pk[1], pk[2], pk[3]);
    stsm4t(pa + 2048, pk[4], pk[5], pk[6], pk[7]);
    fence_async_smem();
}

__device__ __forceinline__ void warp_max(const float (&sc)[16], uint32_t a, int lane) {
    float v[8];
#pragma unroll
    for (int n = 0; n < 8; n++) v[n] = fmaxf(sc[4 * (n >> 1) + (n & 1)], sc[4 * (n >> 1) + 2 + (n & 1)]);
    sts_f(a, reduce8<true>(v, lane));
}

__device__ __forceinline__ void pv_block(float (&o)[4][16], uint32_t sb, int s, int wg) {
    const uint32_t da = make_desc(sb + OFF_C + s * 65536 + wg * 32768), db = make_desc(sb + OFF_P + s * 4096);
    wg_fence();
#pragma unroll
    for (int i = 0; i < 4; i++) {
#pragma unroll
        for (int k = 0; k < 4; k++) wgmma32<1>(o[i], da + ((i * 8192 + k * 2048) >> 4), db + ((k * 32) >> 4));
        wg_commit();
    }
}

__device__ __forceinline__ bool mbar_test(uint32_t bar) {
    uint32_t r;
    asm volatile("{\n.reg .pred p;\nmbarrier.test_wait.parity.shared::cta.b64 p, [%1], 0;\nselp.u32 %0, 1, 0, p;\n}" : "=r"(r) : "r"(bar) : "memory");
    return r;
}

__device__ __forceinline__ void rescale(float (&o)[4][16], uint32_t mxa, int t) {
    const float m0 = max4(lds_f4(mxa));
    const float al = ex2(m0 - fmaxf(m0, max4(lds_f4(mxa + 512))));
#pragma unroll
    for (int jj = 0; jj < 4; jj++) {
        const float a0 = __shfl_sync(~0u, al, 8 * jj + t), a1 = __shfl_sync(~0u, al, 8 * jj + 4 + t);
#pragma unroll
        for (int i = 0; i < 4; i++) {
            o[i][4 * jj] *= a0; o[i][4 * jj + 1] *= a1;
            o[i][4 * jj + 2] *= a0; o[i][4 * jj + 3] *= a1;
        }
    }
}

__device__ __forceinline__ uint32_t ord_flip(uint32_t i) { return i ^ (((int)i >> 31) & 0x7FFFFFFF); }

__device__ __forceinline__ void wait_count1(const uint32_t* p, uint32_t v, uint32_t want, int& it) {
#pragma unroll 1
    while (v != want) {
        v = ld_x32(p);
        spin_check(it);
    }
}

__device__ __forceinline__ uint32_t frag_off(int b, int k) {
    return (k >> 5) * 256 + b * 64 + ((k >> 1) & 3) * 16 + ((k >> 3) & 3) * 4 + (k & 1) * 2;
}

template <int NK, bool FRAG>
__device__ __forceinline__ void gemv_publish(const uint4 (&a)[NK], uint32_t bbase, uint4* dst, uint32_t own, int t, uint32_t tag2) {
    uint4 bv[(NK + 1) / 2];
#pragma unroll
    for (int k2 = 0; k2 < (NK + 1) / 2; k2++) bv[k2] = FRAG ? lds_u4(bbase + k2 * 256) : ldsm4(bbase + k2 * 64);
    float c[4][4] = {};
#pragma unroll
    for (int k = 0; k < NK; k++)
        mma16816(c[k & 3], a[k].x, a[k].y, a[k].z, a[k].w, (k & 1) ? bv[k >> 1].z : bv[k >> 1].x, (k & 1) ? bv[k >> 1].w : bv[k >> 1].y);
    if (t < 2) {
        const uint4 v = tag4((c[0][0] + c[1][0]) + (c[2][0] + c[3][0]), (c[0][1] + c[1][1]) + (c[2][1] + c[3][1]),
                             (c[0][2] + c[1][2]) + (c[2][2] + c[3][2]), (c[0][3] + c[1][3]) + (c[2][3] + c[3][3]), tag2);
        st_x(dst, v);
        sts_u4(own, v);
    }
    __syncwarp();
}

template <class F>
__device__ __forceinline__ void gather_sum(uint32_t sb, const uint4* src, int j, int ww, int lane, uint32_t tag2, int& it, int slot, F&& overlap) {
    const int g = lane >> 2, t = lane & 3;
    uint4 x[2];
    if (t != j) {
        x[0] = ld_x(src);
        x[1] = ld_x(src + 8);
    } else {
        x[0] = lds_u4(sb + OFF_STAGE + ww * 256 + g * 16);
        x[1] = lds_u4(sb + OFF_STAGE + ww * 256 + g * 16 + 128);
    }
    overlap();
#pragma unroll 1
    while (__any_sync(~0u, (tag_bad(x[0], tag2) | tag_bad(x[1], tag2)) & 3)) {
        if (t != j) {
            x[0] = ld_x(src);
            x[1] = ld_x(src + 8);
        }
        spin_check(it);
    }
    const bool hi = t & 2, od = t & 1;
#pragma unroll
    for (int i = 0; i < 2; i++) {
        const float a0 = __uint_as_float(hi ? x[i].z : x[i].x) + __shfl_xor_sync(~0u, __uint_as_float(hi ? x[i].x : x[i].z), 2);
        const float a1 = __uint_as_float(hi ? x[i].w : x[i].y) + __shfl_xor_sync(~0u, __uint_as_float(hi ? x[i].y : x[i].w), 2);
        const float r = (od ? a1 : a0) + __shfl_xor_sync(~0u, od ? a0 : a1, 1);
        sts_u16(sb + OFF_QS + frag_off(2 * (g & 1) + (t & 1), 16 * ww + 4 * i + (g >> 1) + 8 * (t >> 1)), pack_bf16(r, r));
    }
}

struct OutTile {
    uint4 a[8];
    float y[4], gate0, gate1;
    uint32_t abase, dst;
    __device__ __forceinline__ void setup(uint32_t sb, int cta, int mt, int lane) {
        const int g = lane >> 2, t = lane & 3, lq = lane >> 3, li = lane & 7;
        const uint32_t ya = sb + OFF_Y + (2 * (t & 1) * MQ + 16 * mt + g) * 4;
#pragma unroll
        for (int i = 0; i < 4; i++) {
            const uint32_t q = ya + (i & 1) * (MQ * 4) + (i >> 1) * 32;
            y[i] = lds_f(q) + lds_f(q + 4 * MQ * 4);
        }
        gate0 = lds_f(sb + OFF_GATE + (t & 1) * 8);
        gate1 = lds_f(sb + OFF_GATE + (t & 1) * 8 + 4);
        abase = sb + OFF_C + (8 * (lq >> 1) + li) * WOP + 32 * mt + 16 * (lq & 1);
        dst = (((cta & 3) * 18 + 2 * mt + (g >> 2)) * NH + (cta >> 2)) * 8 + 2 * (g & 3) + t;
        asm volatile("" : "+r"(dst), "+r"(abase));
    }
    __device__ __forceinline__ void prefetch(uint32_t sb) {
        mbar_wait(sb + OFF_BAR + 8 * BAR_WO);
#pragma unroll
        for (int k = 0; k < 8; k++) a[k] = ldsm4t(abase + k * (16 * WOP));
    }
    __device__ __forceinline__ void finish(uint32_t sb, Scratch* s, int mt, int lane, uint32_t tag2 TLARG) {
        bar_sync(7, 288);
        if (mt == 0 && lane == 0) TL(45);
        const uint32_t bbase = sb + OFF_QS + ((lane >> 2) & 3) * 64 + (lane & 3) * 16;
        uint4 bv[4];
#pragma unroll
        for (int k2 = 0; k2 < 4; k2++) bv[k2] = lds_u4(bbase + k2 * 256);
        float c0[4] = {}, c1[4] = {}, c2[4] = {}, c3[4] = {};
#pragma unroll
        for (int k2 = 0; k2 < 2; k2++) {
            mma16816(c0, a[2 * k2].x, a[2 * k2].y, a[2 * k2].z, a[2 * k2].w, bv[k2].x, bv[k2].y);
            mma16816(c1, a[2 * k2 + 1].x, a[2 * k2 + 1].y, a[2 * k2 + 1].z, a[2 * k2 + 1].w, bv[k2].z, bv[k2].w);
            mma16816(c2, a[2 * k2 + 4].x, a[2 * k2 + 4].y, a[2 * k2 + 4].z, a[2 * k2 + 4].w, bv[k2 + 2].x, bv[k2 + 2].y);
            mma16816(c3, a[2 * k2 + 5].x, a[2 * k2 + 5].y, a[2 * k2 + 5].z, a[2 * k2 + 5].w, bv[k2 + 2].z, bv[k2 + 2].w);
        }
#pragma unroll
        for (int e = 0; e < 4; e++) {
            c0[e] += c2[e];
            c1[e] += c3[e];
        }
        if ((lane & 3) < 2)
            st_x(&s->e5[dst], tag4(fmaf(c0[0] + c1[0], gate0, y[0]), fmaf(c0[1] + c1[1], gate1, y[1]),
                           fmaf(c0[2] + c1[2], gate0, y[2]), fmaf(c0[3] + c1[3], gate1, y[3]), tag2));
    }
};

__global__ void __cluster_dims__(2, 1, 1) __launch_bounds__(NTHREADS, 1)
fused_decode_kernel(const Params p, const __grid_constant__ CUtensorMap map_q, const __grid_constant__ CUtensorMap map_uk,
                    const __grid_constant__ CUtensorMap map_c, const __grid_constant__ CUtensorMap map_uv,
                    const __grid_constant__ CUtensorMap map_o) {
    extern __shared__ __align__(1024) uint8_t smem_raw[];
    const uint32_t sb = smem_u32(smem_raw);
    const int tid = (SWAP && threadIdx.x < 512) ? (threadIdx.x ^ 256) : threadIdx.x;
    const int lane = tid & 31, g = lane >> 2, t = lane & 3;
    const int warp = __shfl_sync(~0u, tid >> 5, 0);
    const int cta = blockIdx.x, h = cta >> 2, j = cta & 3;
    const int rank = cta & 1;
    const uint32_t bars = sb + OFF_BAR;

    if (warp < 8) {
        const int wg = warp >> 2, w = warp & 3;
        const int b = cta >> 5;
        {
            const int i2 = tid + 256;
            const __nv_bfloat16* base = p.x;
            int off = i2;
            if (i2 >= 288) { base = p.gate_w; off = i2 - 288; }
            if (i2 >= 360) { base = p.w1; off = i2 - 360 + h * (FPH / 8); }
            if (i2 >= 378) { base = p.b1; off = i2 - 378 + h * (FPH / 8); }
            if (i2 >= 396) { base = p.w2; off = i2 - 396 + h * (FPH / 8); }
            const __nv_bfloat16* s2 = base + off * 8;
            cp_async16(sb + OFF_X + tid * 16, p.x + tid * 8);
            if (i2 < 414) cp_async16(sb + OFF_X + i2 * 16, s2);
            if (tid >= 224) sts_f4(sb + OFF_MX + 512 + (tid - 224) * 16, -INFINITY, -INFINITY, -INFINITY, -INFINITY);
        }
        cluster_arrive();
        asm volatile("setmaxnreg.inc.sync.aligned.u32 %0;" ::"n"(REG_A));
        asm volatile("cp.async.wait_all;" ::: "memory");
        bar_sync(6, NSTART);
        if (tid == 0) TL(18);
        {
            const uint32_t xa = sb + OFF_X + (warp >> 1) * (DM * 2);
            const int m0 = (warp & 1) * 32 + lane;
            const float x0 = lds_bf(xa);
            float xr[3];
#pragma unroll
            for (int i = 0; i < 3; i++) xr[i] = lds_bf(xa + (MQ * j + min(m0 + 64 * i, MQ - 1)) * 2);
            float s1 = 0.f, s2 = 0.f, d = 0.f;
#pragma unroll
            for (int i = 0; i < 5; i++) {
                if (i < 4 || !(warp & 1)) {
                    const uint32_t xw = lds_u32(xa + (m0 + 64 * i) * 4), gw = lds_u32(sb + OFF_GW + (m0 + 64 * i) * 4);
                    const float a = bf_lo(xw), c = bf_hi(xw);
                    d = fmaf(a, bf_lo(gw), fmaf(c, bf_hi(gw), d));
                    s1 += (a - x0) + (c - x0);
                    s2 = fmaf(a - x0, a - x0, fmaf(c - x0, c - x0, s2));
                }
            }
#pragma unroll
            for (int o = 16; o; o >>= 1) {
                s1 += __shfl_xor_sync(~0u, s1, o);
                s2 += __shfl_xor_sync(~0u, s2, o);
                d += __shfl_xor_sync(~0u, d, o);
            }
            if (lane == 0) sts_f4(sb + OFF_STAT + warp * 16, s1, s2, d, 0.f);
            TLM(60);
            bar_sync(2, 256);
            const float4 pa = lds_f4(sb + OFF_STAT + (warp >> 1) * 32), pb = lds_f4(sb + OFF_STAT + (warp >> 1) * 32 + 16);
            const float mean = (pa.x + pb.x) * (1.f / DM);
            const float rstd = rsq_fast(fmaxf(fmaf(-mean, mean, (pa.y + pb.y) * (1.f / DM)), 0.f) + 1e-5f);
            const float gate = rcp_fast(1.f + ex2(-1.4426950408889634f * (pa.z + pb.z)));
            if (lane == 0) sts_f(sb + OFF_GATE + (warp >> 1) * 4, gate);
#pragma unroll
            for (int i = 0; i < 3; i++) {
                const float hh = (xr[i] - x0 - mean) * rstd;
                if (m0 + 64 * i < MQ)
                    sts_u4(sb + OFF_MA + ((warp >> 1) * MQ + m0 + 64 * i) * 16,
                           make_uint4(0x3F80u, split_bf16(hh), split_bf16(hh * hh), split_bf16(hh * hh * hh)));
            }
            TLM(14);
            bar_sync(5, 416);
            if (tid == 0) { TL(51); }
            uint4 ra[9];
            float acc[9][2];
#pragma unroll
            for (int i = 0; i < 9; i++) {
                ra[i] = ldsm4(sb + OFF_MA + ((warp >> 1) * MQ + 16 * i + (lane & 15)) * 16);
                acc[i][0] = acc[i][1] = 0.f;
            }
            if (lane == 0) mbar_arrive(bars + 8 * BAR_MA);
            uint32_t ba = sb + OFF_MB + ((warp & 1) * 72 + g) * 64 + t * 16;
            uint4 bn = lds_u4(ba);
            float ksum = 0.f;
#pragma unroll 1
            for (int nt = 0; nt < NTMAX; nt++) {
                const uint4 bv = bn;
                ba += 512;
                bn = lds_u4(ba);
                ksum += bf_lo(bv.z) + bf_lo(bv.w);
#pragma unroll
                for (int i = 0; i < 9; i++) {
                    float u[4] = {}, av[4] = {};
                    mma16816(u, ra[i].x, ra[i].y, ra[i].z, ra[i].w, bv.x, bv.y);
                    mma16816(av, ra[i].x, ra[i].y, ra[i].z, ra[i].w, bv.z, bv.w);
                    acc[i][0] = fmaf(av[0], tanh_fast(u[0]), fmaf(av[1], tanh_fast(u[1]), acc[i][0]));
                    acc[i][1] = fmaf(av[2], tanh_fast(u[2]), fmaf(av[3], tanh_fast(u[3]), acc[i][1]));
                }
            }
            if (tid == 0) { TL(52); }
            ksum += __shfl_xor_sync(~0u, ksum, 4);
            ksum += __shfl_xor_sync(~0u, ksum, 8);
            ksum += __shfl_xor_sync(~0u, ksum, 16);
            const uint32_t ks = split_bf16(0.25f * ksum);
            const uint32_t kb0 = __byte_perm(ks, 0, 0x1010), kb1 = __byte_perm(ks, 0, 0x3232);
            const uint32_t ya = sb + OFF_Y + (((warp & 1) * 4 + (warp >> 1)) * MQ + g + 8 * (t >> 1)) * 4;
            mbar_wait(bars + 8 * BAR_MA);
#pragma unroll
            for (int i = 0; i < 9; i++) {
                float lin[4] = {};
                mma16816(lin, ra[i].x, ra[i].y, ra[i].z, ra[i].w, kb0, kb1);
                const float v0 = acc[i][0] + lin[0], v1 = acc[i][1] + lin[2];
                const float y = ((t & 2) ? v1 : v0) + __shfl_xor_sync(~0u, (t & 2) ? v0 : v1, 2);
                const float yy = (y + __shfl_xor_sync(~0u, y, 1)) * (1.f - gate);
                if ((t & 1) == 0) sts_f(ya + 64 * i, yy);
            }
        }
        if (tid == 0) TL(12);

        cluster_wait();
        const uint32_t mxa = sb + OFF_MX + (8 * (g >> 1) + 2 * t + (g & 1)) * 16;
        const uint32_t pa = sb + OFF_P + wg * 4096 + (8 * (lane >> 4) + (lane & 7)) * 128 + (((2 * w + ((lane >> 3) & 1)) ^ (lane & 7)) << 4);
        float o[4][16], sc[16], v[8], mr[8];
#pragma unroll
        for (int i = 0; i < 4; i++)
#pragma unroll
            for (int k = 0; k < 16; k++) o[i][k] = 0.f;
        mbar_wait(bars + 8 * BAR_Q);
        if (tid == 0) TL(13);
        const uint32_t epoch = lds_u32(sb + OFF_EPOCH), tag = epoch & 1;
        int nq = 0, it = 0;
#pragma unroll 1
        for (uint32_t par = 1;; par ^= 1) {
#pragma unroll
            for (int k = 0; k < 16; k++) sc[k] = 0.f;
            if (wg == 0) {
#pragma unroll 1
                for (int q = 0; q < 4; q++) {
                    mbar_wait(bars + 8 * (BAR_C + q));
                    score_piece(sc, sb, 0, q);
                }
            }
            uint32_t bad = 0;
#pragma unroll
            for (int i = 0; i < 8; i++) bad |= tag_bad(lds_u4(sb + OFF_Q + tid * 16 + i * 4096), tag);
            if (wg == 0) {
                wg_wait<0>();
                reg_fence(sc);
                bar_arrive(5, 256);
                if (tid == 0) TL(15);
                warp_max(sc, mxa + w * 4, lane);
                bar_sync(3, 256);
                const float m0 = max4(lds_f4(mxa));
#pragma unroll
                for (int n = 0; n < 8; n++) mr[n] = __shfl_sync(~0u, m0, 4 * n + t);
                store_p(sc, mr, v, pa);
            } else {
                bar_arrive(3, 256);
                bar_sync(5, 256);
                nq = 0;
#pragma unroll 1
                while (nq < 4 && !bar_or(1 + 8, 128, !mbar_test(bars + 8 * (BAR_C + 4 + nq)))) {
                    score_piece(sc, sb, 1, nq);
                    nq++;
                }
                wg_wait<0>();
                reg_fence(sc);
            }
            if (!bar_or(2, 256, bad & 1)) break;
            if (tid == 0) {
                mbar_expect_tx(bars + 8 * BAR_Q, 32768);
                bulk_load(sb + OFF_Q, &p.s->e2[(rank * 4 + b) * 2048], 32768, bars + 8 * BAR_Q);
            }
            mbar_wait(bars + 8 * BAR_Q, par);
            spin_check(it);
        }
        if (tid == 0) TL(16);
        pv_block(o, sb, 0, wg);
        if (wg == 0) sts_f(mxa + 1024 + w * 4, reduce8<false>(v, lane));
        wg_wait<0>();
#pragma unroll
        for (int i = 0; i < 4; i++) reg_fence(o[i]);
        if (lane == 0) {
            mbar_arrive(bars + 8 * BAR_C0FREE);
            asm volatile("mbarrier.arrive.relaxed.cluster.shared::cluster.b64 _, [%0];" ::"r"(map_peer(bars + 8 * BAR_PF, rank ^ 1)) : "memory");
        }
        if (tid == 0) TL(17);
        if (wg == 1) {
#pragma unroll 1
            for (; nq < 4; nq++) {
                mbar_wait(bars + 8 * (BAR_C + 4 + nq));
                score_piece(sc, sb, 1, nq);
            }
            mbar_wait(bars + 8 * BAR_PF);
            const float m0 = max4(lds_f4(mxa));
#pragma unroll
            for (int n = 0; n < 8; n++) mr[n] = __shfl_sync(~0u, m0, 4 * n + t);
            wg_wait<0>();
            reg_fence(sc);
            if (tid == 128) TL(19);
            store_p(sc, mr, v, pa);
            const float tot = ((v[0] + v[1]) + (v[2] + v[3])) + ((v[4] + v[5]) + (v[6] + v[7]));
            if (bar_or(2, 256, !(tot <= LAZY_LIMIT))) {
                warp_max(sc, mxa + 512 + w * 4, lane);
                bar_sync(3, 256);
                const float m1 = fmaxf(m0, max4(lds_f4(mxa + 512)));
#pragma unroll
                for (int n = 0; n < 8; n++) mr[n] = __shfl_sync(~0u, m1, 4 * n + t);
                rescale(o, mxa, t);
                store_p(sc, mr, v, pa);
                bar_sync(2, 256);
            }
        } else {
            mbar_wait(bars + 8 * BAR_PF);
            if (bar_or(2, 256, false)) {
                bar_sync(3, 256);
                rescale(o, mxa, t);
                bar_sync(2, 256);
            }
        }
        if (tid == 0) { TL(20); TLG(59); mbar_arrive(bars + 8 * BAR_LATE); }
        pv_block(o, sb, 1, wg);
        {
            {
                int lv = lane;
                asm volatile("" : "+r"(lv));
                const int pr = (cta >> 1) & 15;
                uint2* dst = reinterpret_cast<uint2*>(&p.s->e3[((16 * rank + 2 * (lv & 3)) * 4 + 2 * wg + (w >> 1)) * 1024 + (b * 16 + pr) * 8]) + (w & 1) * 8 + (lv >> 2);
                uint32_t* cnt = &p.s->c3[((b * 2 + rank) * 8 + 4 * wg + 2 * (w >> 1)) * 32];
                const uint32_t pd = map_peer(sb + OFF_PD + tid * 16, rank ^ 1), pbar = map_peer(bars + 8 * BAR_PD, rank ^ 1);
                if (wg == 1) {
                    sts_f(mxa + 1536 + w * 4, reduce8<false>(v, lane));
                    bar_arrive(4, 160);
                }
                float fo[4], fp[4];
#pragma unroll
                for (int i = 0; i < 4; i++) {
                    if (i == 0) wg_wait<3>(); else if (i == 1) wg_wait<2>(); else if (i == 2) wg_wait<1>(); else wg_wait<0>();
                    reg_fence(o[i]);
                    if (i == 0) TLM(37);
                    if (i == 3) TLM(21);
                    st_peer4(pd + i * 4096, pack_bf16(o[i][8], o[i][10]), pack_bf16(o[i][9], o[i][11]),
                             pack_bf16(o[i][12], o[i][14]), pack_bf16(o[i][13], o[i][15]), pbar + (i >> 1) * 8);
                    if (i == FACT_AT) {
                        mbar_wait(bars + 8 * BAR_PM);
                        if (tid == 0) TL(9);
                        const int hd = 8 * (g >> 1) + 2 * t + (g & 1);
                        const float mo = lds_f(sb + OFF_PM + hd * 4), mp = lds_f(sb + OFF_PM + 128 + hd * 4);
                        const float mm = fmaxf(mo, mp), ao = ex2(mo - mm), ap = ex2(mp - mm);
#pragma unroll
                        for (int n = 0; n < 4; n++) {
                            fo[n] = __shfl_sync(~0u, ao, 4 * n + t);
                            fp[n] = __shfl_sync(~0u, ap, 4 * n + t);
                        }
                    }
                }
                TLM(5);
#pragma unroll
                for (int hp = 0; hp < 2; hp++) {
                    mbar_wait(bars + 8 * (BAR_PD + hp));
                    if (tid == 0) TL(hp ? 63 : 62);
                    const uint4 r0 = lds_u4(sb + OFF_PD + hp * 8192 + tid * 16), r1 = lds_u4(sb + OFF_PD + hp * 8192 + 4096 + tid * 16);
                    const uint32_t rw[8] = {r0.x, r0.y, r0.z, r0.w, r1.x, r1.y, r1.z, r1.w};
#pragma unroll
                    for (int n = 0; n < 4; n++) {
                        const int a = 4 * (n >> 1) + (n & 1);
                        float v[4];
#pragma unroll
                        for (int q = 0; q < 4; q++) {
                            const float own = o[2 * hp + (q >> 1)][a + 2 * (q & 1)];
                            const uint32_t wv = rw[4 * (q >> 1) + n];
                            v[q] = fmaf(own, fo[n], ((q & 1) ? bf_hi(wv) : bf_lo(wv)) * fp[n]);
                        }
                        st_x64(dst + (8 * (n >> 1) + (n & 1)) * 8 * 1024 + hp * 1024, make_uint2(set_tag<1>(pack_bf16(v[0], v[1]), tag), pack_bf16(v[2], v[3])));
                    }
                    __syncwarp();
                    if (lane == 0) red_add1(cnt + hp * 32);
                }
            }
        }
        TLM(22);
        if (warp == 0) {
            OutTile ot;
            ot.setup(sb, cta, 8, lane);
            ot.prefetch(sb);
            ot.finish(sb, p.s, 8, lane, tag + 1 TLPASS);
        }
    } else if (warp < 16) {
        if (REG_W > 96) asm volatile("setmaxnreg.inc.sync.aligned.u32 %0;" ::"n"(REG_W));
        const int ww = warp - 8, wt = tid - 256;
        const int lq = lane >> 3, li = lane & 7;
        const int b3 = ww >> 1, hp = ww & 1;
        const uint32_t* c3p = &p.s->c3[((b3 * 2 + (h >> 4)) * 8 + 2 * j + hp) * 32];
        cluster_arrive();
        if (t < 2) {
            const uint4 z = make_uint4(0, 0, 0, 0);
            st_x(&p.s->e4[cta * 128 + ww * 16 + 2 * g + t], z);
            uint4* d5 = &p.s->e5[((j * 18 + 2 * ww + (g >> 2)) * NH + h) * 8 + 2 * (g & 3) + t];
            st_x(d5, z);
            if (ww == 0) st_x(d5 + 16 * NH * 8, z);
        }
        bar_sync(6, NSTART);
        if (wt < FPH) {
            const uint32_t ra = sb + OFF_RAW + wt * 2;
            const float w1 = lds_bf(ra), bb = lds_bf(ra + 288), w2h = 0.5f * lds_bf(ra + 576);
            const float c1 = 0.7978845608028654f, c3 = c1 * 0.044715f;
            const uint32_t al[4] = {split_bf16(bb * fmaf(c3 * bb, bb, c1)), split_bf16(w1 * fmaf(3.f * c3 * bb, bb, c1)),
                                    split_bf16(3.f * c3 * w1 * w1 * bb), split_bf16(c3 * w1 * w1 * w1)};
            const uint32_t kk[2] = {split_bf16(w2h * bb), split_bf16(w2h * w1)};
#pragma unroll
            for (int q = 0; q < 4; q++)
                sts_u4(sb + OFF_MB + wt * 64 + q * 16,
                       make_uint4(__byte_perm(al[q], 0, 0x1010), __byte_perm(al[q], 0, 0x3232),
                                  q < 2 ? __byte_perm(kk[q & 1], 0, 0x1010) : 0u, q < 2 ? __byte_perm(kk[q & 1], 0, 0x3232) : 0u));
        }
        TLM(32);
        if (ww < 5) bar_arrive(5, 416);
        int it = 0;
        const uint32_t own = sb + OFF_STAGE + ww * 256 + (2 * g + t) * 16;
        const uint32_t arow = (8 * (lq >> 1) + li) * 128;
        const uint32_t aoff = arow + (((2 * (ww & 3) + (lq & 1)) ^ li) << 4);

        cluster_wait();
        {
            float c[4][4] = {};
#pragma unroll
            for (int q = 0; q < 2; q++) {
                const uint32_t bbase = sb + OFF_X + ((li & 3) * DM + 288 * rank + 144 * q) * 2 + lq * 16;
                uint4 bv[5];
#pragma unroll
                for (int k2 = 0; k2 < 5; k2++) bv[k2] = ldsm4(bbase + k2 * 64);
                if (WQSLEEP && q == 0) while (!mbar_test(bars + 8 * (BAR_WQ + (ww >> 2)))) __nanosleep(WQSLEEP);
                mbar_wait(bars + 8 * ((q ? BAR_WQ2 : BAR_WQ) + (ww >> 2)));
                if (wt == 0 && q == 0) TL(30);
#pragma unroll
                for (int k = 0; k < 9; k++) {
                    const uint4 a = ldsm4t(sb + OFF_WQ + (2 * q + (ww >> 2)) * 18432 + aoff + k * 2048);
                    mma16816(c[k & 3], a.x, a.y, a.z, a.w, (k & 1) ? bv[k >> 1].z : bv[k >> 1].x, (k & 1) ? bv[k >> 1].w : bv[k >> 1].y);
                }
            }
            if (lane == 0) mbar_arrive(bars + 8 * BAR_WQFREE);
            float v[4];
#pragma unroll
            for (int e = 0; e < 4; e++) v[e] = (c[0][e] + c[1][e]) + (c[2][e] + c[3][e]);
            const uint32_t slot = sb + OFF_PQ + ww * 256 + (2 * g + t) * 16;
            if (t < 2)
                st_peer4(map_peer(slot, rank ^ 1), __float_as_uint(v[0]), __float_as_uint(v[1]), __float_as_uint(v[2]), __float_as_uint(v[3]),
                         map_peer(bars + 8 * BAR_PQ, rank ^ 1));
            TLM(39);
            mbar_wait(bars + 8 * BAR_PQ);
            if (t < 2) {
                const float4 o = lds_f4(slot);
                const uint32_t lo = pack_bf16(v[0] + o.x, v[1] + o.y), hi = pack_bf16(v[2] + o.z, v[3] + o.w);
                const uint32_t qa = sb + OFF_QS + frag_off(2 * t, 16 * ww + g);
                sts_u16(qa, lo);
                sts_u16(qa + 64, lo >> 16);
                sts_u16(qa + 4, hi);
                sts_u16(qa + 68, hi >> 16);
            }
            TLM(43);
        }
        const uint32_t epoch = lds_u32(sb + OFF_EPOCH), tag = epoch & 1, tag2 = tag + 1;
        bar_sync(1, 256);
        if (wt == 0) TL(2);

        {
            mbar_wait(bars + 8 * BAR_WK);
            mbar_wait(bars + 8 * (BAR_WK + 1));
            if (wt == 0) TL(1);
            float c0[4] = {}, c1[4] = {};
            const uint32_t abase = sb + OFF_WUV + (16 * ww + 8 * (lq & 1) + li) * 128;
            const uint32_t bbase = sb + OFF_QS + (g & 3) * 64 + t * 16;
#pragma unroll
            for (int k2 = 0; k2 < 4; k2++) {
                const uint4 bv = lds_u4(bbase + k2 * 256);
                const uint4 a0 = ldsm4(abase + (k2 >> 1) * 16384 + (((4 * (k2 & 1) + (lq >> 1)) ^ li) << 4));
                const uint4 a1 = ldsm4(abase + (k2 >> 1) * 16384 + (((4 * (k2 & 1) + 2 + (lq >> 1)) ^ li) << 4));
                mma16816(c0, a0.x, a0.y, a0.z, a0.w, bv.x, bv.y);
                mma16816(c1, a1.x, a1.y, a1.z, a1.w, bv.z, bv.w);
            }
            const float sc = 0.08838834764831845f * 1.4426950408889634f;
            const uint32_t stg = sb + OFF_STAGE + ww * 256;
            stsm2t(stg + li * 32 + (lq & 1) * 16, pack_bf16((c0[0] + c1[0]) * sc, (c0[1] + c1[1]) * sc),
                   pack_bf16((c0[2] + c1[2]) * sc, (c0[3] + c1[3]) * sc));
            __syncwarp();
            if (lane < 16) {
                uint4 v = lds_u4(stg + (lane & 7) * 16);
                v.x = set_tag<1>(v.x, tag);
                v.z = set_tag<1>(v.z, tag);
                st_x(&p.s->e2[(lane >> 1) * 2048 + (2 * j + (ww >> 2)) * 256 + (h ^ (2 * (lane & 8))) * 8 + ((2 * (ww & 3) + (lane & 1)) ^ (h & 7))], v);
            }
            TLM(44);
            bar_sync(1, 256);
            if (wt == 0) {
                red_add1(p.s->c2);
                mbar_arrive(bars + 8 * BAR_WKFREE);
            }
        }
        if (wt == 0) TL(3);
        const float b2v = ldg_bf(p.b2);

        OutTile ot;
        uint32_t e4w = cta * 128 + ww * 16 + 2 * g + t, e4r = ((cta & ~3) + t) * 128 + ww * 16 + g;
        asm volatile("" : "+r"(e4w), "+r"(e4r));
        mbar_wait(bars + 8 * (BAR_UV + (ww >> 2)));
        uint4 auv[8];
#pragma unroll
        for (int k = 0; k < 8; k++) auv[k] = ldsm4t(sb + OFF_WUV + (ww >> 2) * 16384 + aoff + k * 2048);
        mbar_wait(bars + 8 * BAR_LATE);
        if (wt == 0) TL(4);
        uint32_t e3o = (cta * 2 + hp) * 512 + (b3 * 16 + 2 * t) * 8 + g, sto = ((b3 * 2 + (h >> 4)) * 16 + (lane >> 1)) * 16 + (h & 15);
        uint32_t bma = sb + OFF_BM + frag_off(b3, 64 * hp + 32 * (t & 1) + 16 * (g >> 2) + 2 * (g & 3) + (t >> 1));
        asm volatile("" : "+r"(e3o), "+r"(sto), "+r"(bma));
        wait_count1(c3p, lds_u32(sb + OFF_EPOCH + 4 + ww * 4), epoch * 32, it);
        const uint4* e3r = &p.s->e3[e3o];
        const uint2* stat_p = &p.s->stats[sto];
        TLM(6);
        {
            uint4 v[4];
            uint2 st;
            const int it0 = it;
            (void)it0;
#pragma unroll 1
            for (;;) {
                st = ld_x64(stat_p);
                v[0] = ld_x(e3r);
                v[1] = ld_x(e3r + 8);
                v[2] = ld_x(e3r + 64);
                v[3] = ld_x(e3r + 72);
                if (!__any_sync(~0u, ((st.y ^ tag) | tag_bad(v[0], tag) | tag_bad(v[1], tag) | tag_bad(v[2], tag) | tag_bad(v[3], tag)) & 1)) break;
                spin_check(it);
            }
            const float mm = __uint_as_float(ord_flip(__reduce_max_sync(~0u, (int)st.x)));
            const float wp = ex2(__uint_as_float(ord_flip(st.x)) - mm);
            const uint32_t pr = pack_bf16(wp, __shfl_down_sync(~0u, wp, 2));
            const uint32_t wa0 = __shfl_sync(~0u, pr, 4 * t), wa1 = __shfl_sync(~0u, pr, 4 * t + 16);
            float ls = wp * __uint_as_float(st.y);
#pragma unroll
            for (int o = 16; o > 1; o >>= 1) ls += __shfl_xor_sync(~0u, ls, o);
            const float inv = rcp_fast(ls);
            TLM(46);
            float lo[4], hi[4];
#pragma unroll
            for (int wd = 0; wd < 4; wd++) {
                const uint32_t r0 = (&v[0].x)[wd], r1 = (&v[1].x)[wd], r2 = (&v[2].x)[wd], r3 = (&v[3].x)[wd];
                float c[4] = {};
                mma16816(c, __byte_perm(r0, r1, 0x5410), __byte_perm(r0, r1, 0x7632), __byte_perm(r2, r3, 0x5410), __byte_perm(r2, r3, 0x7632), wa0, wa1);
                lo[wd] = c[0];
                hi[wd] = c[2];
            }
            const float l = (t & 2) ? ((t & 1) ? lo[3] : lo[2]) : ((t & 1) ? lo[1] : lo[0]);
            const float u = (t & 2) ? ((t & 1) ? hi[3] : hi[2]) : ((t & 1) ? hi[1] : hi[0]);
            const uint32_t pk = pack_bf16(l * inv, u * inv);
            sts_u16(bma, pk);
            sts_u16(bma + 4, pk >> 16);
        }
        TLM(7);
        if (wt == 0) TLG(61);

        {
            bar_sync(1, 256);
        if (wt == 0) TL(8);
            gemv_publish<8, true>(auv, sb + OFF_BM + (g & 3) * 64 + t * 16, &p.s->e4[e4w], own, t, tag2);
            TLM(40);
            gather_sum(sb, &p.s->e4[e4r], j, ww, lane, tag2, it, 56, [&] {
                ot.setup(sb, cta, ww, lane);
                ot.prefetch(sb);
            });
        }
        TLM(42);

        ot.finish(sb, p.s, ww, lane, tag2 TLPASS);
        TLM(10);

        if (cta < 72 && ww == 1) {
            const uint4* src = &p.s->e5[(cta * NH + lq) * 8 + li];
            const int bb = 2 * (lane & 1) + (lq & 1);
            const float bias = (1.f - lds_f(sb + OFF_GATE + bb * 4)) * b2v;
            uint4 v[8];
#pragma unroll 1
            for (;;) {
#pragma unroll
                for (int i = 0; i < 8; i++) v[i] = ld_x(src + i * 32);
                uint32_t bad = 0;
#pragma unroll
                for (int i = 0; i < 8; i++) bad |= tag_bad(v[i], tag2);
                if (!__any_sync(~0u, bad & 3)) break;
                spin_check(it);
            }
            if (lane == 0) { TL(47); TLV(48, it - it0 + 1); TLV(58, ((uint32_t)clock() - c0_) / (uint32_t)(it - it0 + 1)); }
            float x[4];
#pragma unroll
            for (int e = 0; e < 4; e++)
                x[e] = ((__uint_as_float((&v[0].x)[e]) + __uint_as_float((&v[1].x)[e])) + (__uint_as_float((&v[2].x)[e]) + __uint_as_float((&v[3].x)[e]))) +
                       ((__uint_as_float((&v[4].x)[e]) + __uint_as_float((&v[5].x)[e])) + (__uint_as_float((&v[6].x)[e]) + __uint_as_float((&v[7].x)[e])));
            const bool hi = lane & 16, od = lane & 8;
            const float a0 = (hi ? x[2] : x[0]) + __shfl_xor_sync(~0u, hi ? x[0] : x[2], 16);
            const float a1 = (hi ? x[3] : x[1]) + __shfl_xor_sync(~0u, hi ? x[1] : x[3], 16);
            const float r = (od ? a1 : a0) + __shfl_xor_sync(~0u, od ? a0 : a1, 8);
            const int line = cta % 18;
            p.out[bb * DM + (cta / 18) * MQ + 16 * (line >> 1) + 4 * (line & 1) + (li >> 1) + 8 * (lq >> 1)] = __float2bfloat16(r + bias);
            if (lane == 0) TL(11);
        }
        if (wt == 32) st_x32(&p.s->epoch[cta * 32], epoch);
    } else {
        if (warp == 17 && lane == 0 && EARLYDESC) {
            asm volatile("prefetch.tensormap [%0];" ::"l"(&map_q) : "memory");
            asm volatile("prefetch.tensormap [%0];" ::"l"(&map_uk) : "memory");
        }
        if (warp == 16) {
            if (lane == 0) TL(33);
            uint64_t pol;
            asm volatile("createpolicy.fractional.L2::evict_first.b64 %0, 1.0;" : "=l"(pol));
            if (lane == 0) {
#pragma unroll
                for (int n = 0; n < 2; n++) {
                    mbar_init(bars + 8 * (BAR_WQ + n), 1);
                    mbar_init(bars + 8 * (BAR_WQ2 + n), 1);
                }
                fence_async_smem();
                TL(34);
#pragma unroll
                for (int n = 0; n < 4; n++) {
                    const int q = (n >> 1) ^ ((j >> 1) & WQSWAP);
                    const uint32_t bar = bars + 8 * ((q ? BAR_WQ2 : BAR_WQ) + (n & 1));
                    mbar_expect_tx(bar, 18432);
                    tma3(sb + OFF_WQ + (2 * q + (n & 1)) * 18432, &map_q, h * 128 + 64 * (n & 1), 288 * rank + 144 * q, 0, bar, pol);
                }
                TL(35);
            }
            __syncwarp();
        }
        asm volatile("setmaxnreg.dec.sync.aligned.u32 %0;" ::"n"(REG_P));
        if (warp == 16) {
            const uint64_t t_begin = gtime();
            uint64_t pol;
            asm volatile("createpolicy.fractional.L2::evict_first.b64 %0, 1.0;" : "=l"(pol));
            if (lane == 0) {
#pragma unroll
                for (int i = 2; i < NBAR; i++)
                    if (i != BAR_WQ2 && i != BAR_WQ2 + 1) mbar_init(bars + 8 * i, i == BAR_C0FREE || i == BAR_PF || i == BAR_WQFREE || i == BAR_MA ? 8 : i == BAR_PQ ? 2 : 1);
                mbar_expect_tx(bars + 8 * BAR_PM, 256);
                mbar_expect_tx(bars + 8 * BAR_PL, 128);
                mbar_expect_tx(bars + 8 * BAR_PQ, 2048);
                mbar_expect_tx(bars + 8 * BAR_PD, 8192);
                mbar_expect_tx(bars + 8 * (BAR_PD + 1), 8192);
                asm volatile("fence.mbarrier_init.release.cluster;" ::: "memory");
                fence_async_smem();
            }
            __syncwarp();
            bar_arrive(6, NSTART);
            cluster_arrive();
            const int n = BAR_WK + (int)((ORDER >> (4 * (lane & 15))) & 15);
            const CUtensorMap* mp;
            int c0, c1, c2, wait2 = -1;
            uint32_t dst, bytes = 16384;
            if (n < BAR_C) {
                mp = &map_uk; c0 = h * 128 + 64 * (n - BAR_WK); c1 = 0; c2 = 2 * j; dst = OFF_WUV + (n - BAR_WK) * 16384;
            } else if (n < BAR_UV) {
                mp = &map_c; c0 = 0; c1 = cta * 128 + 64 * ((n - BAR_C) >> 2); c2 = 2 * (n & 3); dst = OFF_C + (n - BAR_C) * 16384;
                if (n == BAR_C + 3) wait2 = BAR_WQFREE;
            } else if (n < BAR_WO) {
                wait2 = BAR_WKFREE;
                mp = &map_uv; c0 = h * 128 + 64 * (n - BAR_UV); c1 = 32 * (j & 1); c2 = 4 * (j >> 1); dst = OFF_WUV + (n - BAR_UV) * 16384;
            } else {
                mp = &map_o; c0 = MQ * j; c1 = h * 128 + 32 * (n - BAR_WO); c2 = 0; dst = OFF_C + (n - BAR_WO) * (32 * WOP); bytes = 32 * WOP;
                if (n == BAR_WO) wait2 = BAR_C0FREE;
            }
            const int nwo = __popc(__ballot_sync(~0u, n >= BAR_WO && lane < 16) & ((1u << lane) - 1));
            int before = 36864 + 16384 * (lane - nwo) + 9216 * nwo;
            before += (((cta >> 1) * 37 + (cta & 1) * 32) & 63) * (bytes / 64) * PHASE / 8;
            if (n >= BAR_WO) before += TAILGAP;
            const uint64_t due = t_begin + (uint64_t)(n == BAR_WK ? WKT0 : n == BAR_WK + 1 ? WKT1 : max(0, (int)(before * (1.f / RATE)) - LEAD));
            const uint32_t fb = bars + 8 * (n > BAR_WO ? BAR_WO : n);
            const uint32_t expect = n == BAR_WO ? 4 * 32 * WOP : n > BAR_WO ? 0 : bytes;
            const bool early = n >= BAR_C + RELEASE && n < BAR_UV;
            const int wprev = __shfl_sync(~0u, n, max(lane - WMAX, 0));
            const int wait1 = lane >= WMAX ? min(wprev, BAR_WO) : -1;
            if (lane == 1) {
                asm volatile("prefetch.tensormap [%0];" ::"l"(&map_c) : "memory");
                asm volatile("prefetch.tensormap [%0];" ::"l"(&map_uv) : "memory");
                asm volatile("prefetch.tensormap [%0];" ::"l"(&map_o) : "memory");
            }
#pragma unroll 1
            for (int k = 0; k < NPIECE - BAR_WK; k++) {
                if (lane == k) {
                    int it = 0;
#pragma unroll 1
                    while (gtime() < due && !(early && mbar_test(bars + 8 * BAR_Q))) spin_check(it);
                    if (wait1 >= 0) mbar_wait(bars + 8 * wait1);
                    if (wait2 >= 0) mbar_wait(bars + 8 * wait2);
                    if (expect) mbar_expect_tx(fb, expect);
                    tma3(sb + dst, mp, c0, c1, c2, fb, pol);
                }
                __syncwarp();
            }
        }
        else if (warp == 17) {
            uint32_t c2v = ld_x32(p.s->c2);
            const uint32_t first = ld_x32(lane == 0 ? &p.s->epoch[cta * 32]
                                                    : &p.s->c3[((((lane - 1) >> 1 & 3) * 2 + (h >> 4)) * 8 + 2 * j + ((lane - 1) & 1)) * 32]);
            cluster_arrive();
            bar_sync(6, NSTART);
            if (lane < 9) asm volatile("st.shared.u32 [%0], %1;" ::"r"(sb + OFF_EPOCH + lane * 4), "r"(first + (lane == 0)) : "memory");
            __syncwarp();
            cluster_wait();
            if (lane == 0) {
                mbar_arrive(bars + 8 * BAR_PQ);
                mbar_wait(bars + 8 * BAR_WKFREE);
                const uint32_t want = (first + 1) * NCTA;
                int it = 0;
#pragma unroll 1
                while (c2v != want) {
                    c2v = ld_x32(p.s->c2);
                    spin_check(it);
                }
                TL(41);
                mbar_expect_tx(bars + 8 * BAR_Q, 32768);
                bulk_load(sb + OFF_Q, &p.s->e2[(rank * 4 + (cta >> 5)) * 2048], 32768, bars + 8 * BAR_Q);
            }
            __syncwarp();
            mbar_wait(bars + 8 * BAR_LATE);
            const uint32_t a = sb + OFF_MX + lane * 16;
            const float m0 = max4(lds_f4(a)), m1 = fmaxf(m0, max4(lds_f4(a + 512)));
            st_peer1(map_peer(sb + OFF_PM + 128 + (lane ^ 16) * 4, rank ^ 1), m1, map_peer(bars + 8 * BAR_PM, rank ^ 1));
            st_peer1(map_peer(sb + OFF_PM + lane * 4, rank), m1, map_peer(bars + 8 * BAR_PM, rank));
            bar_sync(4, 160);
            const float l = fmaf(sum4(lds_f4(a + 1024)), ex2(m0 - m1), sum4(lds_f4(a + 1536)));
            st_peer1(map_peer(sb + OFF_PL + (lane ^ 16) * 4, rank ^ 1), l, map_peer(bars + 8 * BAR_PL, rank ^ 1));
            mbar_wait(bars + 8 * BAR_PM);
            mbar_wait(bars + 8 * BAR_PL);
            const float mp = lds_f(sb + OFF_PM + 128 + lane * 4), mm = fmaxf(m1, mp);
            const float lp = fmaf(l, ex2(m1 - mm), lds_f(sb + OFF_PL + lane * 4) * ex2(mp - mm));
            if (lane < 16)
                st_x64(&p.s->stats[(((cta >> 5) * 2 + rank) * 16 + ((cta >> 1) & 15)) * 16 + lane],
                       make_uint2(ord_flip(__float_as_uint(mm)), set_tag<1>(__float_as_uint(lp), lds_u32(sb + OFF_EPOCH) & 1)));
        }
    }
}

typedef CUresult (*EncodeFn)(CUtensorMap*, CUtensorMapDataType, cuuint32_t, void*, const cuuint64_t*, const cuuint64_t*,
                             const cuuint32_t*, const cuuint32_t*, CUtensorMapInterleave, CUtensorMapSwizzle,
                             CUtensorMapL2promotion, CUtensorMapFloatOOBfill);

void make_map3(EncodeFn enc, CUtensorMap* m, const void* base, uint64_t d0, uint64_t d1, uint64_t d2, uint64_t s1, uint64_t s2,
               uint32_t b0, uint32_t b1, uint32_t b2, CUtensorMapSwizzle sw = CU_TENSOR_MAP_SWIZZLE_128B) {
    cuuint64_t dims[3] = {d0, d1, d2}, strides[2] = {s1, s2};
    cuuint32_t box[3] = {b0, b1, b2}, es[3] = {1, 1, 1};
    enc(m, CU_TENSOR_MAP_DATA_TYPE_BFLOAT16, 3, const_cast<void*>(base), dims, strides, box, es, CU_TENSOR_MAP_INTERLEAVE_NONE,
        sw, CU_TENSOR_MAP_L2_PROMOTION_L2_128B, CU_TENSOR_MAP_FLOAT_OOB_FILL_NONE);
}

}

extern "C" void kernel_launch(void* const* d_in, const int* in_sizes, int n_in, void* d_out, int out_size) {
    (void)in_sizes; (void)n_in; (void)out_size;
    static EncodeFn enc = nullptr;
    static void* scratch = nullptr;
    if (!enc) {
        void* fn = nullptr;
        cudaDriverEntryPointQueryResult qr;
        cudaGetDriverEntryPoint("cuTensorMapEncodeTiled", &fn, cudaEnableDefault, &qr);
        enc = reinterpret_cast<EncodeFn>(fn);
        cudaGetSymbolAddress(&scratch, g_scratch);
        cudaFuncSetAttribute(fused_decode_kernel, cudaFuncAttributeMaxDynamicSharedMemorySize, SMEM_BYTES);
    }
    CUtensorMap mq, mc, muk, muv, mo;
    make_map3(enc, &mc, d_in[1], 64, (uint64_t)NB * SK, 8, DC * 2, 128, 64, 64, 2);
    make_map3(enc, &mq, d_in[2], NH * DH, DM, 1, NH * DH * 2, (uint64_t)DM * NH * DH * 2, 64, 144, 1);
    make_map3(enc, &muk, d_in[3], NH * DH, 64, 8, NH * DH * 2, (uint64_t)64 * NH * DH * 2, 64, 64, 2);
    make_map3(enc, &muv, d_in[4], NH * DH, 64, 8, NH * DH * 2, (uint64_t)64 * NH * DH * 2, 64, 32, 4);
    make_map3(enc, &mo, d_in[5], DM, NH * DH, 1, DM * 2, (uint64_t)DM * NH * DH * 2, WOP / 2, 32, 1, CU_TENSOR_MAP_SWIZZLE_NONE);
    Params p;
    p.x = static_cast<const __nv_bfloat16*>(d_in[0]);
    p.w1 = static_cast<const __nv_bfloat16*>(d_in[7]);
    p.b1 = static_cast<const __nv_bfloat16*>(d_in[8]);
    p.w2 = static_cast<const __nv_bfloat16*>(d_in[9]);
    p.b2 = static_cast<const __nv_bfloat16*>(d_in[10]);
    p.gate_w = static_cast<const __nv_bfloat16*>(d_in[11]);
    p.out = static_cast<__nv_bfloat16*>(d_out);
    p.s = static_cast<Scratch*>(scratch);
    fused_decode_kernel<<<NCTA, NTHREADS, SMEM_BYTES>>>(p, mq, muk, mc, muv, mo);
}
```
